```python
import torch

def _softmax(x, axis=-1):
    return torch.softmax(x, dim=axis)
def _gelu(x):
    return torch.nn.functional.gelu(x, approximate="tanh")
def _silu(x):
    return torch.nn.functional.silu(x)
def _sigmoid(x):
    return torch.sigmoid(x)
def _layernorm(x, axis=-1, eps=1e-5):
    m = x.mean(dim=axis, keepdim=True)
    v = x.var(dim=axis, keepdim=True, unbiased=False)
    return (x - m) / torch.sqrt(v + eps)
def _scatter_add(tgt, idx, src, axis=0):
    return tgt.clone().index_add_(axis, idx, src)
def _segment_sum(src, seg, n):
    out = torch.zeros((n,) + src.shape[1:], dtype=src.dtype)
    return out.index_add_(0, seg, src)
def _pad(x, pw):
    flat = tuple(v for pair in reversed(pw) for v in pair)
    return torch.nn.functional.pad(x, flat)

kernel_name = 'gated_mix__linear_kernel_hedgehog__mixer_token_mlp__prompt'

def setup_inputs():

    _w = (lambda a: (lambda t: t.to(torch.bfloat16) if t.is_floating_point() else t)(torch.as_tensor(a)))
    def _A_setup():
        B, S, D, H = 1, 2048, 1024, 32
        Dh = D // H
        return {
            "x": _w((lambda *s: torch.randn(*s, dtype=torch.bfloat16) * 0.05)(B, S, D)),
            "wqkv": _w((lambda *s: torch.randn(*s, dtype=torch.bfloat16) * 0.8)(D, 3 * D)),
            "w_phi": _w((lambda *s: torch.randn(*s, dtype=torch.bfloat16) * 0.8)(H, Dh, Dh) * (Dh ** -0.5)),
            "wo": _w((lambda *s: torch.randn(*s, dtype=torch.bfloat16) * 0.05)(D, D)),
        }
    _A_in = _A_setup()

    def _B_setup():
        B, S, D, F = 1, 2048, 1024, 3584
        return {
            "x": _w((lambda *s: torch.randn(*s, dtype=torch.bfloat16) * 0.05)(B, S, D)),
            "w1": _w((lambda *s: torch.randn(*s, dtype=torch.bfloat16) * 0.8)(S, F) * (S ** -0.5)),
            "b1": _w((lambda *s: torch.randn(*s, dtype=torch.bfloat16) * 12.8)(F) * 0.02),
            "w2": _w((lambda *s: torch.randn(*s, dtype=torch.bfloat16) * 0.05)(F, S) * (F ** -0.5)),
            "b2": _w((lambda *s: torch.randn(*s, dtype=torch.bfloat16) * 0.8)(S) * 0.02),
        }
    _B_in = _B_setup()

    return {
        "A_x": _A_in["x"],
        "A_wqkv": _A_in["wqkv"],
        "A_w_phi": _A_in["w_phi"],
        "A_wo": _A_in["wo"],
        "B_x": _B_in["x"],
        "B_w1": _B_in["w1"],
        "B_b1": _B_in["b1"],
        "B_w2": _B_in["w2"],
        "B_b2": _B_in["b2"],
        "gate_w": _w((lambda *s: torch.randn(*s, dtype=torch.bfloat16) * 0.05)(1024) * 16.0),
    }

def reference(A_x, A_wqkv, A_w_phi, A_wo, B_x, B_w1, B_b1, B_w2, B_b2, gate_w):
    def _A_ref(x, wqkv, w_phi, wo):
        B, S, D = x.shape
        H = 32; Dh = D // H
        qkv = (lambda x, *d: x.permute(*d))((x @ wqkv).reshape(B, S, 3, H, Dh), 2, 0, 3, 1, 4)
        q, k, v = qkv[0], qkv[1], qkv[2]
        pq = torch.einsum("bhsd,hdf->bhsf", q, w_phi)
        pk = torch.einsum("bhsd,hdf->bhsf", k, w_phi)
        phi_q = torch.concatenate([_softmax(pq, axis=-1), _softmax(-pq, axis=-1)], axis=-1)
        phi_k = torch.concatenate([_softmax(pk, axis=-1), _softmax(-pk, axis=-1)], axis=-1)
        kv = torch.einsum("bhsf,bhsd->bhfd", phi_k, v)
        z  = torch.einsum("bhsf->bhf", phi_k)
        num = torch.einsum("bhqf,bhfd->bhqd", phi_q, kv)
        den = torch.einsum("bhqf,bhf->bhq", phi_q, z)[..., None] + 1e-6
        o = num / den
        return (lambda x, *d: x.permute(*d))(o, 0, 2, 1, 3).reshape(B, S, D) @ wo

    def _B_ref(x, w1, b1, w2, b2):
        B, S, D = x.shape
        h = _layernorm(x, axis=-1)
        u = torch.einsum("bsd,sf->bdf", h, w1) + b1
        u = _gelu(u)
        y = torch.einsum("bdf,fs->bds", u, w2) + b2
        return (lambda x, *d: x.permute(*d))(y, 0, 2, 1)

    x = A_x
    g = _sigmoid((x * gate_w).sum(-1, keepdims=True))
    a = _A_ref(x, A_wqkv, A_w_phi, A_wo)
    b = _B_ref(x, B_w1, B_b1, B_w2, B_b2)
    return g * a + (1 - g) * b
```

```cpp
#include <cuda_runtime.h>
#include <cuda_bf16.h>
#include <cuda.h>
#include <stdint.h>

namespace {

constexpr int S_ = 2048, D_ = 1024, F_ = 3584;
constexpr int NCTA = 128;

constexpr uint32_t RING_BYTES = 163840;
constexpr uint32_t PQ_OFF = 147456;
constexpr uint32_t STG_OFF = RING_BYTES;
constexpr uint32_t STG_BYTES = 57344;
constexpr uint32_t WPHI_OFF = STG_OFF + STG_BYTES;
constexpr uint32_t B1_OFF = WPHI_OFF + 8192;
constexpr uint32_t GATE_OFF = B1_OFF + 1024;
constexpr uint32_t BAR_OFF = GATE_OFF + 1536;
constexpr uint32_t SMEM_BYTES = BAR_OFF + 256;
constexpr int NB = 8;
constexpr uint32_t BAR_FULL = BAR_OFF, BAR_EMPTY = BAR_OFF + 64, BAR_STG_FULL = BAR_OFF + 128,
                   BAR_STG_EMPTY = BAR_OFF + 136, BAR_WPHI = BAR_OFF + 144, BAR_XFREE = BAR_OFF + 152,
                   BAR_DEP = BAR_OFF + 160  , BAR_XSENT = BAR_OFF + 192, BAR_XRECV = BAR_OFF + 200, FLAG_OFF = BAR_OFF + 208;
constexpr uint32_t E1_BYTES = 40960, E2_BYTES = 22528, E3_BYTES = 24576, E4_BYTES = 16384;

struct SyncCtr {
  unsigned ln_cnt[32];
  unsigned done[32];
  unsigned u_cnt[8][32];
  unsigned kv_cnt[16][32];
  unsigned kv_rd[16][32];
  unsigned o_cnt[32][32];
  unsigned x_flag[2 * NCTA][32];
};
__device__ SyncCtr g_sync;
__device__ __align__(1024) __nv_bfloat16 g_h[S_ * D_];
__device__ __align__(1024) __nv_bfloat16 g_uT[F_ * D_];
__device__ __align__(1024) __nv_bfloat16 g_oT[D_ * S_];
__device__ __align__(1024) float g_kv[32 * 2560];
__device__ __align__(1024) float g_gate[2 * S_];
__device__ __align__(1024) uint4 g_xch[NCTA * 2048];

#define TS(i) do {} while (0)

struct Params {
  CUtensorMap x, wqkv, h, w1, w2, uT, oT, wo, oT_st, out_st, wphi;
  const __nv_bfloat16* xin;
  const __nv_bfloat16* wqkv_p;
  const __nv_bfloat16* w2_p;
  const __nv_bfloat16* b1;
  const __nv_bfloat16* b2;
  const __nv_bfloat16* gw;
};

__device__ __forceinline__ uint32_t smem_u32(const void* p) { return (uint32_t)__cvta_generic_to_shared(p); }
__device__ __forceinline__ void mbar_init(uint32_t bar, uint32_t count) {
  asm volatile("mbarrier.init.shared::cta.b64 [%0], %1;" ::"r"(bar), "r"(count));
}
__device__ __forceinline__ void mbar_expect_tx(uint32_t bar, uint32_t bytes) {
  asm volatile("mbarrier.arrive.expect_tx.shared::cta.b64 _, [%0], %1;" ::"r"(bar), "r"(bytes) : "memory");
}
__device__ __forceinline__ void mbar_arrive(uint32_t bar) {
  asm volatile("mbarrier.arrive.shared::cta.b64 _, [%0];" ::"r"(bar) : "memory");
}
__device__ __forceinline__ void mbar_arrive_n(uint32_t bar, uint32_t n) {
  asm volatile("mbarrier.arrive.shared::cta.b64 _, [%0], %1;" ::"r"(bar), "r"(n) : "memory");
}
__device__ __forceinline__ uint32_t mapa(uint32_t addr, uint32_t cta) {
  uint32_t r;
  asm volatile("mapa.shared::cluster.u32 %0, %1, %2;" : "=r"(r) : "r"(addr), "r"(cta));
  return r;
}
__device__ __forceinline__ void mbar_arrive_remote(uint32_t remote_bar) {
  asm volatile("mbarrier.arrive.shared::cluster.b64 _, [%0];" ::"r"(remote_bar) : "memory");
}
__device__ __forceinline__ bool mbar_try_wait(uint32_t bar, uint32_t parity) {
  uint32_t ok;
  asm volatile("{\n.reg .pred p;\nmbarrier.try_wait.parity.shared::cta.b64 p, [%1], %2;\nselp.u32 %0, 1, 0, p;\n}\n"
               : "=r"(ok) : "r"(bar), "r"(parity) : "memory");
  return ok;
}
constexpr uint32_t SPIN_LIMIT = 1u << 24;
__device__ __forceinline__ void mbar_wait(uint32_t bar, uint32_t parity, uint32_t& bud) {
  while (!mbar_try_wait(bar, parity)) {
    if (++bud > SPIN_LIMIT) break;
  }
}
__device__ __forceinline__ void mbar_wait_cluster(uint32_t bar, uint32_t parity, uint32_t& bud) {
  uint32_t ok;
  do {
    asm volatile("{\n.reg .pred p;\nmbarrier.try_wait.parity.acquire.cluster.shared::cta.b64 p, [%1], %2;\nselp.u32 %0, 1, 0, p;\n}\n"
                 : "=r"(ok) : "r"(bar), "r"(parity) : "memory");
    if (++bud > SPIN_LIMIT) break;
  } while (!ok);
}
__device__ __forceinline__ void tma_load_2d(uint32_t dst, const CUtensorMap* tm, uint32_t bar, int c0, int c1) {
  asm volatile("cp.async.bulk.tensor.2d.shared::cluster.global.mbarrier::complete_tx::bytes [%0], [%1, {%3, %4}], [%2];"
               ::"r"(dst), "l"(tm), "r"(bar), "r"(c0), "r"(c1) : "memory");
}
__device__ __forceinline__ void tma_load_3d(uint32_t dst, const CUtensorMap* tm, uint32_t bar, int c0, int c1, int c2) {
  asm volatile("cp.async.bulk.tensor.3d.shared::cluster.global.mbarrier::complete_tx::bytes [%0], [%1, {%3, %4, %5}], [%2];"
               ::"r"(dst), "l"(tm), "r"(bar), "r"(c0), "r"(c1), "r"(c2) : "memory");
}
__device__ __forceinline__ void tma_load_3d_mc(uint32_t dst, const CUtensorMap* tm, uint32_t bar, int c0, int c1, int c2, uint16_t mask) {
  asm volatile("cp.async.bulk.tensor.3d.shared::cluster.global.mbarrier::complete_tx::bytes.multicast::cluster [%0], [%1, {%3, %4, %5}], [%2], %6;"
               ::"r"(dst), "l"(tm), "r"(bar), "r"(c0), "r"(c1), "r"(c2), "h"(mask) : "memory");
}
__device__ __forceinline__ void tma_store_2d(const CUtensorMap* tm, uint32_t src, int c0, int c1) {
  asm volatile("cp.async.bulk.tensor.2d.global.shared::cta.bulk_group [%0, {%2, %3}], [%1];"
               ::"l"(tm), "r"(src), "r"(c0), "r"(c1) : "memory");
}
__device__ __forceinline__ void bulk_load(uint32_t dst, const void* src, uint32_t bytes, uint32_t bar) {
  asm volatile("cp.async.bulk.shared::cluster.global.mbarrier::complete_tx::bytes [%0], [%1], %2, [%3];"
               ::"r"(dst), "l"(src), "r"(bytes), "r"(bar) : "memory");
}
__device__ __forceinline__ void bulk_reduce_add_f32(float* dst, uint32_t src, uint32_t bytes) {
  asm volatile("cp.reduce.async.bulk.global.shared::cta.bulk_group.add.f32 [%0], [%1], %2;" ::"l"(dst), "r"(src), "r"(bytes) : "memory");
}
__device__ __forceinline__ bool elect_one() {
  uint32_t p;
  asm volatile("{\n.reg .pred q;\nelect.sync _|q, 0xffffffff;\nselp.u32 %0, 1, 0, q;\n}\n" : "=r"(p));
  return p;
}
__device__ __forceinline__ uint32_t max_bf2(uint32_t a, uint32_t b) { uint32_t r; asm("max.bf16x2 %0, %1, %2;" : "=r"(r) : "r"(a), "r"(b)); return r; }
__device__ __forceinline__ uint32_t min_bf2(uint32_t a, uint32_t b) { uint32_t r; asm("min.bf16x2 %0, %1, %2;" : "=r"(r) : "r"(a), "r"(b)); return r; }
__device__ __forceinline__ void sts128(uint32_t a, uint32_t x, uint32_t y, uint32_t z, uint32_t w) {
  asm volatile("st.shared.v4.u32 [%0], {%1, %2, %3, %4};" ::"r"(a), "r"(x), "r"(y), "r"(z), "r"(w) : "memory");
}
__device__ __forceinline__ void l2_prefetch(const void* p, uint32_t bytes) {
  asm volatile("cp.async.bulk.prefetch.L2.global [%0], %1;" ::"l"(p), "r"(bytes) : "memory");
}
__device__ __forceinline__ void pf_line(const void* p) { asm volatile("prefetch.global.L2 [%0];" ::"l"(p)); }
__device__ __forceinline__ void bulk_commit() { asm volatile("cp.async.bulk.commit_group;" ::: "memory"); }
__device__ __forceinline__ void bulk_wait_all() { asm volatile("cp.async.bulk.wait_group 0;" ::: "memory"); }
__device__ __forceinline__ void bulk_wait_read() { asm volatile("cp.async.bulk.wait_group.read 0;" ::: "memory"); }
__device__ __forceinline__ void prefetch_tmap(const CUtensorMap* tm) {
  asm volatile("prefetch.tensormap [%0];" ::"l"(tm) : "memory");
}
__device__ __forceinline__ void fence_proxy_async() { asm volatile("fence.proxy.async;" ::: "memory"); }
__device__ __forceinline__ void fence_proxy_async_smem() { asm volatile("fence.proxy.async.shared::cta;" ::: "memory"); }
__device__ __forceinline__ void wgmma_fence() { asm volatile("wgmma.fence.sync.aligned;" ::: "memory"); }
__device__ __forceinline__ void wgmma_commit() { asm volatile("wgmma.commit_group.sync.aligned;" ::: "memory"); }
template <int N> __device__ __forceinline__ void wgmma_wait() { asm volatile("wgmma.wait_group.sync.aligned %0;" ::"n"(N) : "memory"); }
__device__ __forceinline__ void cluster_sync_all() {
  asm volatile("barrier.cluster.arrive.release.aligned;\nbarrier.cluster.wait.acquire.aligned;" ::: "memory");
}
__device__ __forceinline__ void cluster_arrive_relaxed() { asm volatile("barrier.cluster.arrive.relaxed.aligned;" ::: "memory"); }
__device__ __forceinline__ void cluster_wait() { asm volatile("barrier.cluster.wait.acquire.aligned;" ::: "memory"); }
__device__ __forceinline__ uint32_t cluster_ctarank() { uint32_t r; asm volatile("mov.u32 %0, %%cluster_ctarank;" : "=r"(r)); return r; }
template <int ID, int N> __device__ __forceinline__ void named_bar() { asm volatile("bar.sync %0, %1;" ::"n"(ID), "n"(N) : "memory"); }
__device__ __forceinline__ uint64_t make_desc(uint32_t addr, uint32_t lbo, uint32_t sbo, uint32_t swz) {
  return (uint64_t)((addr & 0x3FFFF) >> 4) | ((uint64_t)(lbo >> 4) << 16) | ((uint64_t)(sbo >> 4) << 32) | ((uint64_t)swz << 62);
}
template <int R> __device__ __forceinline__ void reg_alloc() { asm volatile("setmaxnreg.inc.sync.aligned.u32 %0;" ::"n"(R)); }
template <int R> __device__ __forceinline__ void reg_dealloc() { asm volatile("setmaxnreg.dec.sync.aligned.u32 %0;" ::"n"(R)); }
__device__ __forceinline__ uint32_t pack_bf16(float lo, float hi) {
  uint32_t r;
  asm("cvt.rn.bf16x2.f32 %0, %1, %2;" : "=r"(r) : "f"(hi), "f"(lo));
  return r;
}
__device__ __forceinline__ float bf_lo(uint32_t v) { return __uint_as_float(v << 16); }
__device__ __forceinline__ float bf_hi(uint32_t v) { return __uint_as_float(v & 0xFFFF0000u); }
__device__ __forceinline__ void stmatrix_x4(uint32_t addr, uint32_t r0, uint32_t r1, uint32_t r2, uint32_t r3) {
  asm volatile("stmatrix.sync.aligned.m8n8.x4.shared.b16 [%0], {%1, %2, %3, %4};" ::"r"(addr), "r"(r0), "r"(r1), "r"(r2), "r"(r3) : "memory");
}
__device__ __forceinline__ void stmatrix_x4_t(uint32_t addr, uint32_t r0, uint32_t r1, uint32_t r2, uint32_t r3) {
  asm volatile("stmatrix.sync.aligned.m8n8.x4.trans.shared.b16 [%0], {%1, %2, %3, %4};" ::"r"(addr), "r"(r0), "r"(r1), "r"(r2), "r"(r3) : "memory");
}
__device__ __forceinline__ void ldmatrix_x4(uint32_t addr, uint32_t (&r)[4]) {
  asm volatile("ldmatrix.sync.aligned.m8n8.x4.shared.b16 {%0, %1, %2, %3}, [%4];" : "=r"(r[0]), "=r"(r[1]), "=r"(r[2]), "=r"(r[3]) : "r"(addr) : "memory");
}
__device__ __forceinline__ void ldmatrix_x4_t(uint32_t addr, uint32_t (&r)[4]) {
  asm volatile("ldmatrix.sync.aligned.m8n8.x4.trans.shared.b16 {%0, %1, %2, %3}, [%4];" : "=r"(r[0]), "=r"(r[1]), "=r"(r[2]), "=r"(r[3]) : "r"(addr) : "memory");
}
__device__ __forceinline__ void mma_bf16(float* d, const uint32_t (&a)[4], uint32_t b0, uint32_t b1) {
  asm volatile("mma.sync.aligned.m16n8k16.row.col.f32.bf16.bf16.f32 {%0, %1, %2, %3}, {%4, %5, %6, %7}, {%8, %9}, {%0, %1, %2, %3};"
               : "+f"(d[0]), "+f"(d[1]), "+f"(d[2]), "+f"(d[3]) : "r"(a[0]), "r"(a[1]), "r"(a[2]), "r"(a[3]), "r"(b0), "r"(b1));
}
__device__ __forceinline__ float tanh_fast(float x) { float r; asm("tanh.approx.f32 %0, %1;" : "=f"(r) : "f"(x)); return r; }
__device__ __forceinline__ uint64_t desc64(uint32_t lo, uint32_t hi) {
  uint64_t d;
  asm("mov.b64 %0, {%1, %2};" : "=l"(d) : "r"(lo), "r"(hi));
  return d;
}
__device__ __forceinline__ unsigned ld_acquire(const unsigned* p) {
  unsigned v;
  asm volatile("ld.acquire.gpu.global.u32 %0, [%1];" : "=r"(v) : "l"(p) : "memory");
  return v;
}
__device__ __forceinline__ void red_release_add(unsigned* p, unsigned v) {
  asm volatile("red.release.gpu.global.add.u32 [%0], %1;" ::"l"(p), "r"(v) : "memory");
}
__device__ __forceinline__ void wait_counter(const unsigned* p, unsigned target, uint32_t& bud) {
  while (ld_acquire(p) < target) {
    __nanosleep(64);
    if (++bud > SPIN_LIMIT) break;
  }
}
__device__ __forceinline__ float ex2(float x) { float r; asm("ex2.approx.ftz.f32 %0, %1;" : "=f"(r) : "f"(x)); return r; }
__device__ __forceinline__ float rcp(float x) { float r; asm("rcp.approx.ftz.f32 %0, %1;" : "=f"(r) : "f"(x)); return r; }

template<int TA, int TB> __device__ __forceinline__ void wgmma_ss_n192(float (&d)[96], uint64_t da, uint64_t db, int scaleD) {
  asm volatile("{\n.reg .pred p;\nsetp.ne.b32 p, %98, 0;\n"
    "wgmma.mma_async.sync.aligned.m64n192k16.f32.bf16.bf16 {%0, %1, %2, %3, %4, %5, %6, %7, %8, %9, %10, %11, %12, %13, %14, %15, %16, %17, %18, %19, %20, %21, %22, %23, %24, %25, %26, %27, %28, %29, %30, %31, %32, %33, %34, %35, %36, %37, %38, %39, %40, %41, %42, %43, %44, %45, %46, %47, %48, %49, %50, %51, %52, %53, %54, %55, %56, %57, %58, %59, %60, %61, %62, %63, %64, %65, %66, %67, %68, %69, %70, %71, %72, %73, %74, %75, %76, %77, %78, %79, %80, %81, %82, %83, %84, %85, %86, %87, %88, %89, %90, %91, %92, %93, %94, %95}, %96, %97, p, 1, 1, %99, %100;\n}\n"
    : "+f"(d[0]), "+f"(d[1]), "+f"(d[2]), "+f"(d[3]), "+f"(d[4]), "+f"(d[5]), "+f"(d[6]), "+f"(d[7]), "+f"(d[8]), "+f"(d[9]), "+f"(d[10]), "+f"(d[11]), "+f"(d[12]), "+f"(d[13]), "+f"(d[14]), "+f"(d[15]), "+f"(d[16]), "+f"(d[17]), "+f"(d[18]), "+f"(d[19]), "+f"(d[20]), "+f"(d[21]), "+f"(d[22]), "+f"(d[23]), "+f"(d[24]), "+f"(d[25]), "+f"(d[26]), "+f"(d[27]), "+f"(d[28]), "+f"(d[29]), "+f"(d[30]), "+f"(d[31]), "+f"(d[32]), "+f"(d[33]), "+f"(d[34]), "+f"(d[35]), "+f"(d[36]), "+f"(d[37]), "+f"(d[38]), "+f"(d[39]), "+f"(d[40]), "+f"(d[41]), "+f"(d[42]), "+f"(d[43]), "+f"(d[44]), "+f"(d[45]), "+f"(d[46]), "+f"(d[47]), "+f"(d[48]), "+f"(d[49]), "+f"(d[50]), "+f"(d[51]), "+f"(d[52]), "+f"(d[53]), "+f"(d[54]), "+f"(d[55]), "+f"(d[56]), "+f"(d[57]), "+f"(d[58]), "+f"(d[59]), "+f"(d[60]), "+f"(d[61]), "+f"(d[62]), "+f"(d[63]), "+f"(d[64]), "+f"(d[65]), "+f"(d[66]), "+f"(d[67]), "+f"(d[68]), "+f"(d[69]), "+f"(d[70]), "+f"(d[71]), "+f"(d[72]), "+f"(d[73]), "+f"(d[74]), "+f"(d[75]), "+f"(d[76]), "+f"(d[77]), "+f"(d[78]), "+f"(d[79]), "+f"(d[80]), "+f"(d[81]), "+f"(d[82]), "+f"(d[83]), "+f"(d[84]), "+f"(d[85]), "+f"(d[86]), "+f"(d[87]), "+f"(d[88]), "+f"(d[89]), "+f"(d[90]), "+f"(d[91]), "+f"(d[92]), "+f"(d[93]), "+f"(d[94]), "+f"(d[95])
    : "l"(da), "l"(db), "r"(scaleD), "n"(TA), "n"(TB));
}

template<int TA, int TB> __device__ __forceinline__ void wgmma_ss_n128(float (&d)[64], uint64_t da, uint64_t db, int scaleD) {
  asm volatile("{\n.reg .pred p;\nsetp.ne.b32 p, %66, 0;\n"
    "wgmma.mma_async.sync.aligned.m64n128k16.f32.bf16.bf16 {%0, %1, %2, %3, %4, %5, %6, %7, %8, %9, %10, %11, %12, %13, %14, %15, %16, %17, %18, %19, %20, %21, %22, %23, %24, %25, %26, %27, %28, %29, %30, %31, %32, %33, %34, %35, %36, %37, %38, %39, %40, %41, %42, %43, %44, %45, %46, %47, %48, %49, %50, %51, %52, %53, %54, %55, %56, %57, %58, %59, %60, %61, %62, %63}, %64, %65, p, 1, 1, %67, %68;\n}\n"
    : "+f"(d[0]), "+f"(d[1]), "+f"(d[2]), "+f"(d[3]), "+f"(d[4]), "+f"(d[5]), "+f"(d[6]), "+f"(d[7]), "+f"(d[8]), "+f"(d[9]), "+f"(d[10]), "+f"(d[11]), "+f"(d[12]), "+f"(d[13]), "+f"(d[14]), "+f"(d[15]), "+f"(d[16]), "+f"(d[17]), "+f"(d[18]), "+f"(d[19]), "+f"(d[20]), "+f"(d[21]), "+f"(d[22]), "+f"(d[23]), "+f"(d[24]), "+f"(d[25]), "+f"(d[26]), "+f"(d[27]), "+f"(d[28]), "+f"(d[29]), "+f"(d[30]), "+f"(d[31]), "+f"(d[32]), "+f"(d[33]), "+f"(d[34]), "+f"(d[35]), "+f"(d[36]), "+f"(d[37]), "+f"(d[38]), "+f"(d[39]), "+f"(d[40]), "+f"(d[41]), "+f"(d[42]), "+f"(d[43]), "+f"(d[44]), "+f"(d[45]), "+f"(d[46]), "+f"(d[47]), "+f"(d[48]), "+f"(d[49]), "+f"(d[50]), "+f"(d[51]), "+f"(d[52]), "+f"(d[53]), "+f"(d[54]), "+f"(d[55]), "+f"(d[56]), "+f"(d[57]), "+f"(d[58]), "+f"(d[59]), "+f"(d[60]), "+f"(d[61]), "+f"(d[62]), "+f"(d[63])
    : "l"(da), "l"(db), "r"(scaleD), "n"(TA), "n"(TB));
}

template<int TA, int TB> __device__ __forceinline__ void wgmma_ss_n96(float (&d)[48], uint64_t da, uint64_t db, int scaleD) {
  asm volatile("{\n.reg .pred p;\nsetp.ne.b32 p, %50, 0;\n"
    "wgmma.mma_async.sync.aligned.m64n96k16.f32.bf16.bf16 {%0, %1, %2, %3, %4, %5, %6, %7, %8, %9, %10, %11, %12, %13, %14, %15, %16, %17, %18, %19, %20, %21, %22, %23, %24, %25, %26, %27, %28, %29, %30, %31, %32, %33, %34, %35, %36, %37, %38, %39, %40, %41, %42, %43, %44, %45, %46, %47}, %48, %49, p, 1, 1, %51, %52;\n}\n"
    : "+f"(d[0]), "+f"(d[1]), "+f"(d[2]), "+f"(d[3]), "+f"(d[4]), "+f"(d[5]), "+f"(d[6]), "+f"(d[7]), "+f"(d[8]), "+f"(d[9]), "+f"(d[10]), "+f"(d[11]), "+f"(d[12]), "+f"(d[13]), "+f"(d[14]), "+f"(d[15]), "+f"(d[16]), "+f"(d[17]), "+f"(d[18]), "+f"(d[19]), "+f"(d[20]), "+f"(d[21]), "+f"(d[22]), "+f"(d[23]), "+f"(d[24]), "+f"(d[25]), "+f"(d[26]), "+f"(d[27]), "+f"(d[28]), "+f"(d[29]), "+f"(d[30]), "+f"(d[31]), "+f"(d[32]), "+f"(d[33]), "+f"(d[34]), "+f"(d[35]), "+f"(d[36]), "+f"(d[37]), "+f"(d[38]), "+f"(d[39]), "+f"(d[40]), "+f"(d[41]), "+f"(d[42]), "+f"(d[43]), "+f"(d[44]), "+f"(d[45]), "+f"(d[46]), "+f"(d[47])
    : "l"(da), "l"(db), "r"(scaleD), "n"(TA), "n"(TB));
}

template<int TA, int TB> __device__ __forceinline__ void wgmma_ss_n40(float (&d)[20], uint64_t da, uint64_t db, int scaleD) {
  asm volatile("{\n.reg .pred p;\nsetp.ne.b32 p, %22, 0;\n"
    "wgmma.mma_async.sync.aligned.m64n40k16.f32.bf16.bf16 {%0, %1, %2, %3, %4, %5, %6, %7, %8, %9, %10, %11, %12, %13, %14, %15, %16, %17, %18, %19}, %20, %21, p, 1, 1, %23, %24;\n}\n"
    : "+f"(d[0]), "+f"(d[1]), "+f"(d[2]), "+f"(d[3]), "+f"(d[4]), "+f"(d[5]), "+f"(d[6]), "+f"(d[7]), "+f"(d[8]), "+f"(d[9]), "+f"(d[10]), "+f"(d[11]), "+f"(d[12]), "+f"(d[13]), "+f"(d[14]), "+f"(d[15]), "+f"(d[16]), "+f"(d[17]), "+f"(d[18]), "+f"(d[19])
    : "l"(da), "l"(db), "r"(scaleD), "n"(TA), "n"(TB));
}

template<int TB> __device__ __forceinline__ void wgmma_rs_n32(float (&d)[16], uint32_t a0, uint32_t a1, uint32_t a2, uint32_t a3, uint64_t db, int scaleD) {
  asm volatile("{\n.reg .pred p;\nsetp.ne.b32 p, %21, 0;\n"
    "wgmma.mma_async.sync.aligned.m64n32k16.f32.bf16.bf16 {%0, %1, %2, %3, %4, %5, %6, %7, %8, %9, %10, %11, %12, %13, %14, %15}, {%16, %17, %18, %19}, %20, p, 1, 1, %22;\n}\n"
    : "+f"(d[0]), "+f"(d[1]), "+f"(d[2]), "+f"(d[3]), "+f"(d[4]), "+f"(d[5]), "+f"(d[6]), "+f"(d[7]), "+f"(d[8]), "+f"(d[9]), "+f"(d[10]), "+f"(d[11]), "+f"(d[12]), "+f"(d[13]), "+f"(d[14]), "+f"(d[15])
    : "r"(a0), "r"(a1), "r"(a2), "r"(a3), "l"(db), "r"(scaleD), "n"(TB));
}

#define XRI 13
#define EXP_PF 7
#define EXP_NW8 8
#define EXP_NW4 4
template <int N> __device__ __forceinline__ void acc_zero(float (&a)[N]) {
#pragma unroll
  for (int i = 0; i < N; i++) asm volatile("mov.f32 %0, 0f00000000;" : "=f"(a[i]));
}

constexpr int NENT = 16 + 64 + 16 + 56 + 32;
struct RingTab {
  unsigned short off16[NENT];
  unsigned char nwait[NENT];
};
constexpr RingTab make_ring_tab() {
  RingTab tb{};
  uint32_t lo[NENT] = {}, hi[NENT] = {};
  uint32_t head = 0;
  int tail = 0;
  for (int e = 0; e < NENT; e++) {
    const uint32_t sz = e < 16 ? E1_BYTES : (e < 80 ? E2_BYTES : (e < 96 ? E1_BYTES : (e < 152 ? E3_BYTES : E4_BYTES)));
    uint32_t off = head;
    if (off + sz > (sz == E1_BYTES ? RING_BYTES : PQ_OFF)) off = 0;
    head = off + sz;
    int need = e - NB;
    for (int t = 0; t < e; t++)
      if (lo[t] < off + sz && off < hi[t] && t > need) need = t;
    lo[e] = off;
    hi[e] = off + sz;
    tb.off16[e] = (unsigned short)(off >> 4);
    int nw = need + 1 - tail;
    if (nw < 0) nw = 0;
    tb.nwait[e] = (unsigned char)nw;
    tail += nw;
  }
  return tb;
}
__constant__ RingTab c_ring = make_ring_tab();

#define NFIRST 1
constexpr uint32_t HI128 = 0x40000040u;
constexpr uint32_t HI64 = 0x80000020u;

template <int PH, int NA, int NBB>
__device__ __forceinline__ void mma_phase(float (&acc)[NA], float (&acc2)[NBB], const int e0, const int n, const uint32_t sbase,
                                          const int wg, const bool elected, const uint32_t peer_empty, uint32_t& bud, const uint32_t own = 0) {
  const uint32_t s16 = (sbase & 0x3FFFF) >> 4;
  const uint32_t a_lo = PH == 1 ? (s16 + wg * 512 + (1u << 16)) : (s16 + wg * 256 + (256u << 16));
  const uint32_t b_lo = PH == 1 ? (s16 + 1024 + (256u << 16)) : (PH == 2 ? (s16 + 512 + (64u << 16)) : (s16 + 512 + (256u << 16)));
#pragma unroll 1
  for (int e = e0; e < e0 + n; e++) {
    const uint32_t o = c_ring.off16[e];
    mbar_wait(sbase + BAR_FULL + 8 * (e & 7), (e >> 3) & 1, bud);
    wgmma_fence();
    if constexpr (PH == 1) {
#pragma unroll
      for (int kk = 0; kk < 4; kk++)
        wgmma_ss_n192<0, 1>(acc, desc64(a_lo + o + kk * 2, HI128), desc64(b_lo + o + (kk >> 1) * 768 + (kk & 1) * 128, HI128), 1);
    } else if constexpr (PH == 2) {
#pragma unroll
      for (int kk = 0; kk < 2; kk++) {
        const uint64_t da = desc64(a_lo + o + kk * 128, HI128);
        wgmma_ss_n128<1, 1>(acc, da, desc64(b_lo + o + kk * 448, HI64), 1);
        wgmma_ss_n96<1, 1>(acc2, da, desc64(b_lo + o + kk * 448 + 256, HI64), 1);
      }
    } else if constexpr (PH == 4) {
#pragma unroll
      for (int kk = 0; kk < 2; kk++)
        wgmma_ss_n128<1, 1>(acc, desc64(a_lo + o + kk * 128, HI128), desc64(b_lo + o + kk * 128, HI128), 1);
    } else {
#pragma unroll
      for (int kk = 0; kk < 2; kk++) {
        const uint64_t da = desc64(a_lo + o + kk * 128, HI128);
        wgmma_ss_n128<1, 1>(acc, da, desc64(b_lo + o + kk * 128 + own, HI128), 1);
        wgmma_ss_n128<1, 1>(acc2, da, desc64(b_lo + o + kk * 128 + (own ^ 512), HI128), 1);
      }
    }
    wgmma_commit();
    wgmma_wait<1>();
    if (elected && e > e0 && e <= NENT - NB) {
      const uint32_t pj = 8 * ((e + 7) & 7);
      mbar_arrive(sbase + BAR_EMPTY + pj);
      mbar_arrive_remote(peer_empty + pj);
    }
  }
  wgmma_wait<0>();
  if (elected && e0 + n <= NENT - NB) {
    const uint32_t pj = 8 * ((e0 + n + 7) & 7);
    mbar_arrive(sbase + BAR_EMPTY + pj);
    mbar_arrive_remote(peer_empty + pj);
  }
}

template <uint32_t SZ> __device__ __forceinline__ uint32_t prod_alloc(int e, int& tail, uint32_t sbase, bool lead, uint32_t& bud) {
  for (int nw = c_ring.nwait[e]; nw > 0; nw--) {
    mbar_wait(sbase + BAR_EMPTY + 8 * (tail & (NB - 1)), (tail >> 3) & 1, bud);
    tail++;
  }
  if (lead) mbar_expect_tx(sbase + BAR_FULL + 8 * (e & (NB - 1)), SZ);
  return sbase + ((uint32_t)c_ring.off16[e] << 4);
}

template <int NR> __device__ __forceinline__ void ln_rows(const Params& P, int row0, int rstep, int lane) {
  uint4 xv[NR][4];
#pragma unroll
  for (int q = 0; q < NR; q++)
#pragma unroll
    for (int i = 0; i < 4; i++) xv[q][i] = __ldg(reinterpret_cast<const uint4*>(P.xin + (size_t)(row0 + q * rstep) * D_) + i * 32 + lane);
  float sum[NR], dot[NR];
#pragma unroll
  for (int q = 0; q < NR; q++) { sum[q] = 0.f; dot[q] = 0.f; }
#pragma unroll
  for (int i = 0; i < 4; i++) {
    const uint4 gv = __ldg(reinterpret_cast<const uint4*>(P.gw) + i * 32 + lane);
    const uint32_t gs[4] = {gv.x, gv.y, gv.z, gv.w};
#pragma unroll
    for (int q = 0; q < NR; q++) {
      const uint32_t xs[4] = {xv[q][i].x, xv[q][i].y, xv[q][i].z, xv[q][i].w};
#pragma unroll
      for (int c = 0; c < 4; c++) {
        const float a = bf_lo(xs[c]), b = bf_hi(xs[c]);
        sum[q] += a + b;
        dot[q] = fmaf(a, bf_lo(gs[c]), dot[q]);
        dot[q] = fmaf(b, bf_hi(gs[c]), dot[q]);
      }
    }
  }
#pragma unroll
  for (int o = 16; o > 0; o >>= 1)
#pragma unroll
    for (int q = 0; q < NR; q++) {
      sum[q] += __shfl_xor_sync(0xffffffffu, sum[q], o);
      dot[q] += __shfl_xor_sync(0xffffffffu, dot[q], o);
    }
  float var[NR];
#pragma unroll
  for (int q = 0; q < NR; q++) {
    sum[q] *= (1.0f / D_);
    var[q] = 0.f;
#pragma unroll
    for (int i = 0; i < 4; i++) {
      const uint32_t xs[4] = {xv[q][i].x, xv[q][i].y, xv[q][i].z, xv[q][i].w};
#pragma unroll
      for (int c = 0; c < 4; c++) {
        const float a = bf_lo(xs[c]) - sum[q], b = bf_hi(xs[c]) - sum[q];
        var[q] = fmaf(a, a, var[q]);
        var[q] = fmaf(b, b, var[q]);
      }
    }
  }
#pragma unroll
  for (int o = 16; o > 0; o >>= 1)
#pragma unroll
    for (int q = 0; q < NR; q++) var[q] += __shfl_xor_sync(0xffffffffu, var[q], o);
#pragma unroll
  for (int q = 0; q < NR; q++) {
    const int row = row0 + q * rstep;
    const float rs = rsqrtf(var[q] * (1.0f / D_) + 1e-5f), mr = -sum[q] * rs;
#pragma unroll
    for (int i = 0; i < 4; i++) {
      const uint32_t xs[4] = {xv[q][i].x, xv[q][i].y, xv[q][i].z, xv[q][i].w};
      uint32_t hs[4];
#pragma unroll
      for (int c = 0; c < 4; c++) hs[c] = pack_bf16(fmaf(bf_lo(xs[c]), rs, mr), fmaf(bf_hi(xs[c]), rs, mr));
      reinterpret_cast<uint4*>(g_h + (size_t)row * D_)[i * 32 + lane] = make_uint4(hs[0], hs[1], hs[2], hs[3]);
    }
    if (lane == 0) {
      const float e = __expf(-fabsf(dot[q]));
      const float big = 1.0f / (1.0f + e), small = e * big;
      g_gate[row] = dot[q] >= 0.f ? big : small;
      g_gate[S_ + row] = dot[q] >= 0.f ? small : big;
    }
  }
}

__device__ __forceinline__ void gelu_pass(uint32_t sbase, __nv_bfloat16* dst, int u) {
  const uint32_t stg = sbase + STG_OFF;
#pragma unroll 2
  for (int i = 0; i < 16; i++) {
    const int id = i * 224 + u;
    int frow = id >> 3, pan = 0;
    if (frow >= 224) { frow -= 224; pan = 64; }
    float bv;
    asm volatile("ld.shared.f32 %0, [%1];" : "=f"(bv) : "r"(sbase + B1_OFF + 4 * frow));
    uint32_t v[4];
    asm volatile("ld.shared.v4.u32 {%0, %1, %2, %3}, [%4];" : "=r"(v[0]), "=r"(v[1]), "=r"(v[2]), "=r"(v[3]) : "r"(stg + id * 16));
#pragma unroll
    for (int c = 0; c < 4; c++) {
      const float u0 = bf_lo(v[c]) + bv, u1 = bf_hi(v[c]) + bv;
      constexpr float C1 = 0.7978845608028654f, C2 = C1 * 0.044715f;
      const float t0 = tanh_fast(u0 * fmaf(u0 * u0, C2, C1)), t1 = tanh_fast(u1 * fmaf(u1 * u1, C2, C1));
      const float h0 = 0.5f * u0, h1 = 0.5f * u1;
      v[c] = pack_bf16(fmaf(h0, t0, h0), fmaf(h1, t1, h1));
    }
    *reinterpret_cast<uint4*>(dst + (size_t)frow * D_ + pan + (((id ^ frow) & 7) << 3)) = make_uint4(v[0], v[1], v[2], v[3]);
  }
}

__device__ __forceinline__ void feature_unit(uint32_t src, uint32_t dst, int unit, int lane) {
  constexpr float L2E = 1.4426950408889634f;
  const int sgn = lane >> 4, hd = (lane >> 3) & 1, r7 = lane & 7, row = unit * 8 + r7;
  const uint32_t flip = sgn ? 0x80008000u : 0u;
  uint32_t x[16];
#pragma unroll
  for (int c = 0; c < 4; c++)
    asm volatile("ld.shared.v4.u32 {%0, %1, %2, %3}, [%4];" : "=r"(x[4 * c]), "=r"(x[4 * c + 1]), "=r"(x[4 * c + 2]), "=r"(x[4 * c + 3])
                 : "r"(src + row * 128 + (((hd * 4 + c) ^ r7) << 4)) : "memory");
  __syncwarp();
#pragma unroll
  for (int i = 0; i < 16; i++) x[i] ^= flip;
  uint32_t ma = max_bf2(x[0], x[1]), mb = max_bf2(x[2], x[3]);
#pragma unroll
  for (int i = 4; i < 16; i += 2) { ma = max_bf2(ma, x[i]); mb = max_bf2(mb, x[i + 1]); }
  ma = max_bf2(ma, mb);
  const float off = -fmaxf(bf_lo(ma), bf_hi(ma)) * L2E;
  float e[32], s0 = 0.f, s1 = 0.f;
#pragma unroll
  for (int i = 0; i < 16; i++) {
    e[2 * i] = ex2(fmaf(bf_lo(x[i]), L2E, off));
    e[2 * i + 1] = ex2(fmaf(bf_hi(x[i]), L2E, off));
    s0 += e[2 * i];
    s1 += e[2 * i + 1];
  }
  const float inv = rcp(s0 + s1);
  const uint32_t d = dst + hd * 16384 + row * 128;
#pragma unroll
  for (int c = 0; c < 4; c++)
    sts128(d + (((sgn * 4 + c) ^ r7) << 4), pack_bf16(e[8 * c] * inv, e[8 * c + 1] * inv), pack_bf16(e[8 * c + 2] * inv, e[8 * c + 3] * inv),
           pack_bf16(e[8 * c + 4] * inv, e[8 * c + 5] * inv), pack_bf16(e[8 * c + 6] * inv, e[8 * c + 7] * inv));
}
__device__ __forceinline__ void feature_range(uint32_t src, uint32_t dst, int u0, int u1, int ustep, int lane) {
#pragma unroll 1
  for (int u = u0; u < u1; u += ustep) feature_unit(src, dst, u, lane);
  fence_proxy_async_smem();
}

#define EXP_MASK 0xFFFF
#define ON(bit) ((EXP_MASK >> (bit)) & 1)
__device__ __forceinline__ void aux_kv_o(const Params& P, uint32_t sbase, int cta, int tile, int hp, int sb, int t, uint32_t& bud,
                                         long long g_tb_local) {
  const uint32_t stg = sbase + STG_OFF;
  const int warp = t >> 5, lane = t & 31, g = lane >> 2, tq = lane & 3;
  {
    float kv[2][20];
    acc_zero(kv[0]); acc_zero(kv[1]);
    if (ON(0)) {
    wgmma_fence();
#pragma unroll
    for (int h = 0; h < 2; h++)
#pragma unroll
      for (int kk = 0; kk < 8; kk++)
        wgmma_ss_n40<1, 1>(kv[h], make_desc(stg + h * 16384 + kk * 2048, 4096, 1024, 1),
                           make_desc(stg + 32768 + h * 8192 + kk * 1024, 16384 - h * 8192, 512, 2), 1);
    wgmma_commit();
    wgmma_wait<0>();
    }
    named_bar<6, 224>();
    if (t == 0) TS(33 + tile * 8);
    if (ON(1)) {
#pragma unroll
    for (int h = 0; h < 2; h++)
#pragma unroll
      for (int j = 0; j < 5; j++)
#pragma unroll
        for (int rh = 0; rh < 2; rh++)
          asm volatile("st.shared.v2.f32 [%0], {%1, %2};" ::"r"(stg + 32768 + h * 10240 + ((warp * 16 + g + 8 * rh) * 40 + 8 * j + 2 * tq) * 4),
                       "f"(kv[h][4 * j + 2 * rh]), "f"(kv[h][4 * j + 2 * rh + 1]) : "memory");
    fence_proxy_async_smem();
    named_bar<1, 128>();
    }
    if (warp == 0) {
      if (t == 0) {
        if (ON(2)) {
          bulk_reduce_add_f32(g_kv + hp * 5120, stg + 32768, 20480);
          bulk_commit();
          bulk_wait_all();
        }
        if (ON(4)) red_release_add(&g_sync.kv_cnt[hp][0], 1);
        TS(34 + tile * 8);
        if (ON(5)) wait_counter(&g_sync.kv_cnt[hp][0], 16, bud);
        TS(35 + tile * 8);
      }
      __syncwarp();
    } else if (ON(3)) {
      feature_range(sbase + PQ_OFF, stg, 8 + warp, 16, 3, lane);
    }
    named_bar<5, 224>();
    if (t == 0) {
      if (tile == 0) {
        mbar_arrive(sbase + BAR_XFREE);
        mbar_arrive_remote(mapa(sbase + BAR_XFREE, cluster_ctarank() ^ 1));
      }
      TS(32 + tile * 8);
    }
  }
  if (ON(6)) {
    float4 v[5][2];
#pragma unroll
    for (int i = 0; i < 5; i++) {
      const float4* src = reinterpret_cast<const float4*>(g_kv + hp * 5120) + (t + 128 * i) * 2;
      v[i][0] = __ldcg(src);
      v[i][1] = __ldcg(src + 1);
    }
#pragma unroll
    for (int i = 0; i < 5; i++) {
      const int idx = t + 128 * i, fr = idx / 5, c = idx - fr * 5;
      sts128(stg + 32768 + fr * 128 + ((c ^ (fr & 7)) << 4), pack_bf16(v[i][0].x, v[i][0].y), pack_bf16(v[i][0].z, v[i][0].w),
             pack_bf16(v[i][1].x, v[i][1].y), pack_bf16(v[i][1].z, v[i][1].w));
    }
  }
  fence_proxy_async_smem();
  named_bar<1, 128>();
  if (t == 0) TS(36 + tile * 8);
  if (t == 0) {
    unsigned old = 0;
    if (ON(8)) old = atomicAdd(&g_sync.kv_rd[hp][0], 1);
    asm volatile("st.shared.u32 [%0], %1;" ::"r"(sbase + FLAG_OFF), "r"(old) : "memory");
  }
  float o[2][2][20];
#pragma unroll
  for (int mb = 0; mb < 2; mb++) { acc_zero(o[mb][0]); acc_zero(o[mb][1]); }
  if (ON(9)) {
  wgmma_fence();
#pragma unroll
  for (int mb = 0; mb < 2; mb++)
#pragma unroll
    for (int h = 0; h < 2; h++)
#pragma unroll
      for (int c = 0; c < 4; c++)
        wgmma_ss_n40<0, 1>(o[mb][h], make_desc(stg + h * 16384 + mb * 8192 + c * 32, 16, 1024, 1),
                           make_desc(stg + 32768 + h * 8192 + c * 2048, 4096, 1024, 1), 1);
  wgmma_commit();
  wgmma_wait<0>();
  }
  named_bar<1, 128>();
  if (t == 0) TS(37 + tile * 8);
  if (ON(10)) {
#pragma unroll
  for (int mb = 0; mb < 2; mb++) {
    const uint32_t pan = stg + mb * 8192;
    float g0, g1;
    asm volatile("ld.shared.f32 %0, [%1];" : "=f"(g0) : "r"(sbase + GATE_OFF + 1024 + 4 * (mb * 64 + warp * 16 + g)));
    asm volatile("ld.shared.f32 %0, [%1];" : "=f"(g1) : "r"(sbase + GATE_OFF + 1024 + 4 * (mb * 64 + warp * 16 + g + 8)));
#pragma unroll
    for (int h = 0; h < 2; h++) {
      const float d0 = __shfl_sync(0xffffffffu, o[mb][h][16], lane & ~3), d1 = __shfl_sync(0xffffffffu, o[mb][h][18], lane & ~3);
      const float s0 = g0 * rcp(d0 + 1e-6f), s1 = g1 * rcp(d1 + 1e-6f);
#pragma unroll
      for (int jj = 0; jj < 2; jj++) {
        const int mi = lane >> 3, i = lane & 7;
        const int jrow = h * 32 + 8 * (2 * jj + (mi >> 1)) + i;
        const int schunk = 2 * warp + (mi & 1);
        const float* q = &o[mb][h][8 * jj];
        stmatrix_x4_t(pan + jrow * 128 + ((schunk ^ (jrow & 7)) << 4), pack_bf16(q[0] * s0, q[1] * s0), pack_bf16(q[2] * s1, q[3] * s1),
                      pack_bf16(q[4] * s0, q[5] * s0), pack_bf16(q[6] * s1, q[7] * s1));
      }
    }
  }
  }
  fence_proxy_async_smem();
  named_bar<1, 128>();
  if (t == 0) TS(38 + tile * 8);
  if (t == 0) {
    if (ON(11)) {
    tma_store_2d(&P.oT_st, stg, sb * 128, hp * 64);
    tma_store_2d(&P.oT_st, stg + 8192, sb * 128 + 64, hp * 64);
    bulk_commit();
    bulk_wait_read();
    }
    mbar_arrive(sbase + BAR_STG_EMPTY);
    bulk_wait_all();
    TS(39 + tile * 8);
    red_release_add(&g_sync.o_cnt[sb * 2 + tile][0], 1);
  }
  uint32_t old;
  asm volatile("ld.shared.u32 %0, [%1];" : "=r"(old) : "r"(sbase + FLAG_OFF) : "memory");
  if (old == 15) {
    float4* dst = reinterpret_cast<float4*>(g_kv + hp * 5120);
    for (int i = t; i < 1280; i += 128) dst[i] = make_float4(0.f, 0.f, 0.f, 0.f);
    if (t == 0) { g_sync.kv_cnt[hp][0] = 0; g_sync.kv_rd[hp][0] = 0; }
  }
}

__device__ __forceinline__ void watch(const unsigned* ctr, unsigned target, uint32_t bar, uint32_t& bud) {
  wait_counter(ctr, target, bud);
  fence_proxy_async();
  mbar_arrive(bar);
}

__device__ __forceinline__ void finish_role() {
  const unsigned old = atomicAdd(&g_sync.done[0], 1);
  if (old == 2 * NCTA - 1) {
    g_sync.ln_cnt[0] = 0;
    for (int i = 0; i < 8; i++) g_sync.u_cnt[i][0] = 0;
    for (int i = 0; i < 32; i++) g_sync.o_cnt[i][0] = 0;
    g_sync.done[0] = 0;
  }
}

__global__ void __cluster_dims__(2, 1, 1) __launch_bounds__(512, 1) fused_kernel(const __grid_constant__ Params P) {
  extern __shared__ __align__(1024) uint8_t smem_raw[];
  const uint32_t sbase = smem_u32(smem_raw);
  const int tid = threadIdx.x, t = tid & 127;
  const int wg = __shfl_sync(0xffffffffu, tid >> 7, 0);
  const uint32_t rank = cluster_ctarank();
  const int cta = blockIdx.x, cl = cta >> 1;
  uint32_t bud = 0;
  const long long g_tb_local = clock64();
  const int sb1 = (cl & 7) * 2 + rank, hpA = cl >> 3, hpB = hpA + 8;
  const int dp2 = cl & 3, fb2 = cl >> 2, db2 = dp2 * 2 + rank;
  const int kh = cl & 1, sb3 = ((cl >> 1) & 7) * 2 + rank, db3 = cl >> 4;

  if (tid >= 384 && tid < 416) {
    if (tid == 384) {
      for (int i = 0; i < NFIRST; i++) mbar_init(sbase + BAR_FULL + 8 * i, 1);
      asm volatile("fence.mbarrier_init.release.cluster;" ::: "memory");
    }
    __syncwarp();
    asm volatile("bar.arrive 0, 512;" ::: "memory");
    if (tid == 384) {
#pragma unroll
      for (int kt = 0; kt < NFIRST; kt++) {
        const uint32_t dst = sbase + kt * E1_BYTES, fb = sbase + BAR_FULL + 8 * kt;
        mbar_expect_tx(fb, E1_BYTES);
        tma_load_2d(dst, &P.x, fb, kt * 64, sb1 * 128);
        tma_load_3d(dst + 16384, &P.wqkv, fb, hpA * 64, kt * 64, 0);
        tma_load_3d(dst + 16384 + 12288, &P.wqkv, fb, hpA * 64, kt * 64 + 32, 0);
      }
    }
    __syncwarp();
  } else {
    if (tid == 416) {
      for (int i = NFIRST; i < NB; i++) mbar_init(sbase + BAR_FULL + 8 * i, 1);
      for (int i = 0; i < NB; i++) mbar_init(sbase + BAR_EMPTY + 8 * i, 4);
      mbar_init(sbase + BAR_STG_FULL, 256);
      mbar_init(sbase + BAR_STG_EMPTY, 1);
      mbar_init(sbase + BAR_WPHI, 1);
      for (int i = 0; i < 4; i++) mbar_init(sbase + BAR_DEP + 8 * i, 1);
      mbar_init(sbase + BAR_XSENT, 256);
      mbar_init(sbase + BAR_XRECV, 1);
      mbar_init(sbase + BAR_XFREE, 2);
      asm volatile("fence.mbarrier_init.release.cluster;" ::: "memory");
    }
    asm volatile("bar.sync 0, 512;" ::: "memory");
  }
  cluster_arrive_relaxed();

  if (wg == 3) {
    reg_dealloc<64>();
    const int warp = __shfl_sync(0xffffffffu, t >> 5, 0), lane = t & 31;
    if (warp == 0) {
      const bool lead = elect_one();
      if (lead) TS(60);
      cluster_wait();
      if (lead) TS(62);
      int e = NFIRST, tail = 0;
#pragma unroll 1
      for (int tile = 0; tile < 2; tile++) {
        const int hp = tile ? hpB : hpA;
        if (tile) mbar_wait(sbase + BAR_XFREE, 0, bud);
#pragma unroll 1
        for (int kt = tile ? 0 : NFIRST; kt < 16; kt++, e++) {
          const uint32_t dst = prod_alloc<E1_BYTES>(e, tail, sbase, lead, bud);
          const uint32_t fb = sbase + BAR_FULL + 8 * (e & (NB - 1));
          if (lead) {
            tma_load_2d(dst, &P.x, fb, kt * 64, sb1 * 128);
            tma_load_3d_mc(dst + 16384 + rank * 12288, &P.wqkv, fb, hp * 64, kt * 64 + rank * 32, 0, 3);
          }
        }
        if (tile == 0) {
          if (lead) TS(20);
          mbar_wait(sbase + BAR_DEP, 0, bud);
          if (lead) TS(21);
#pragma unroll 1
          for (int kt = 0; kt < 64; kt++, e++) {
            const uint32_t dst = prod_alloc<E2_BYTES>(e, tail, sbase, lead, bud);
            const uint32_t fb = sbase + BAR_FULL + 8 * (e & (NB - 1));
            if (lead) {
              tma_load_3d(dst, &P.h, fb, 0, kt * 32, db2 * 2);
              tma_load_3d_mc(dst + 8192 + rank * 7168, &P.w1, fb, 0, kt * 32 + rank * 16, fb2 * 7, 3);
            }
          }
        }
      }
      if (lead) TS(22);
      mbar_wait(sbase + BAR_DEP + 8, 0, bud);
      if (lead) TS(23);
#pragma unroll 1
      for (int kt = 0; kt < 56; kt++, e++) {
        const uint32_t dst = prod_alloc<E3_BYTES>(e, tail, sbase, lead, bud);
        const uint32_t fb = sbase + BAR_FULL + 8 * (e & (NB - 1));
        if (lead) {
          tma_load_3d(dst, &P.w2, fb, 0, kh * 1792 + kt * 32, sb3 * 2);
          tma_load_3d_mc(dst + 8192 + rank * 8192, &P.uT, fb, 0, kh * 1792 + kt * 32, db3 * 4 + rank * 2, 3);
        }
      }
#pragma unroll 1
      for (int q = 0; q < 4; q++) {
        const int half = q & 1, cb = db3 * 4 + ((q >> 1) ^ kh ^ 1) * 2 + rank;
        if (q < 2) {
          if (lead) TS(24 + 3 * half);
          mbar_wait(sbase + BAR_DEP + 16 + 8 * half, 0, bud);
          if (lead) TS(25 + 3 * half);
        }
#pragma unroll 1
        for (int kt = 0; kt < 8; kt++, e++) {
          const uint32_t dst = prod_alloc<E4_BYTES>(e, tail, sbase, lead, bud);
          const uint32_t fb = sbase + BAR_FULL + 8 * (e & (NB - 1));
          if (lead) {
            tma_load_3d(dst, &P.oT, fb, 0, half * 512 + kh * 256 + kt * 32, sb3 * 2);
            tma_load_3d_mc(dst + 8192 + rank * 4096, &P.wo, fb, 0, half * 512 + kh * 256 + kt * 32, cb, 3);
          }
        }
      }
    } else {
      const int hw = warp - 1;
#if !(EXP_PF & 1)
      if (hw == 1) {
#pragma unroll
        for (int i = 0; i < 6; i++) { const int p = i * 4 + (lane >> 3); pf_line(P.wqkv_p + (size_t)(cta * 8 + p / 3) * 3072 + (p % 3) * 1024 + (lane & 7) * 64); }
      }
#endif
      ln_rows<1>(P, cta * 16 + 12 + hw, 0, lane);
      if (hw == 0) ln_rows<1>(P, cta * 16 + 15, 0, lane);
      named_bar<5, 224>();
      const bool watcher = (hw == 2 && lane == 0);
      if (watcher) watch(&g_sync.ln_cnt[0], NCTA, sbase + BAR_DEP, bud);
      __syncwarp();
#pragma unroll 1
      for (int tile = 0; tile < 2; tile++) {
        mbar_wait(sbase + BAR_STG_FULL, 0, bud);
        feature_range(sbase + STG_OFF + 16384, sbase + STG_OFF, hw, 16, 7, lane);
        named_bar<5, 224>();
        named_bar<6, 224>();
        feature_range(sbase + PQ_OFF, sbase + STG_OFF, hw, 9, 3, lane);
        named_bar<5, 224>();
#if !(EXP_PF & 2)
        if (tile == 0 && hw == 1) {
#pragma unroll
          for (int i = 0; i < 6; i++) { const int p = i * 4 + (lane >> 3); pf_line(P.wqkv_p + (size_t)(cta * 8 + p / 3) * 3072 + (p % 3) * 1024 + 512 + (lane & 7) * 64); }
        }
#endif
#if !(EXP_PF & 4)
        if (tile == 0 && hw == 0) {
#pragma unroll 1
          for (int i = 0; i < 28; i++) { pf_line(P.w2_p + (size_t)(cta * 28 + i) * S_ + lane * 64); __nanosleep(200); }
        }
#endif
        if (watcher) watch(&g_sync.o_cnt[sb3 * 2 + tile][0], 8, sbase + BAR_DEP + 16 + 8 * tile, bud);
        __syncwarp();
        if (tile == 0) {
          mbar_wait(sbase + BAR_STG_FULL, 1, bud);
          gelu_pass(sbase, g_uT + (size_t)fb2 * 224 * D_ + db2 * 128, 128 + hw * 32 + lane);
          named_bar<5, 224>();
          if (watcher) watch(&g_sync.u_cnt[db3 * 2 + kh][0], 16, sbase + BAR_DEP + 8, bud);
          __syncwarp();
        }
      }
      if (watcher) finish_role();
    }
  } else if (wg == 2) {
    if (t == 0) TS(11);
    cluster_wait();
    const int warp = t >> 5, lane = t & 31;
    if (t == 0) {
      mbar_expect_tx(sbase + BAR_WPHI, 8192);
      tma_load_2d(sbase + WPHI_OFF, &P.wphi, sbase + BAR_WPHI, 0, hpA * 64);
      tma_load_2d(sbase + WPHI_OFF + 4096, &P.wphi, sbase + BAR_WPHI, 0, hpB * 64);
    }
    ln_rows<3>(P, cta * 16 + warp, 4, lane);
    if (t == 0) TS(26);
    named_bar<5, 224>();
    if (t == 0) red_release_add(&g_sync.ln_cnt[0], 1);
    if (t == 0) TS(12);
    for (int i = t; i < 224; i += 128) {
      const float bv = __bfloat162float(P.b1[fb2 * 224 + i]);
      asm volatile("st.shared.f32 [%0], %1;" ::"r"(sbase + B1_OFF + 4 * i), "f"(bv) : "memory");
    }
    if (t == 0) wait_counter(&g_sync.ln_cnt[0], NCTA, bud);
    named_bar<1, 128>();
    {
      const float mg = __ldcg(g_gate + S_ + sb3 * 128 + t);
      const float b2v = kh ? 0.f : __bfloat162float(P.b2[sb3 * 128 + t]);
      asm volatile("st.shared.f32 [%0], %1;" ::"r"(sbase + GATE_OFF + 4 * t), "f"(mg) : "memory");
      asm volatile("st.shared.f32 [%0], %1;" ::"r"(sbase + GATE_OFF + 512 + 4 * t), "f"(b2v) : "memory");
      asm volatile("st.shared.f32 [%0], %1;" ::"r"(sbase + GATE_OFF + 1024 + 4 * t), "f"(__ldcg(g_gate + sb1 * 128 + t)) : "memory");
    }
#pragma unroll 1
    for (int tile = 0; tile < 2; tile++) {
      mbar_wait(sbase + BAR_STG_FULL, 0, bud);
      feature_range(sbase + STG_OFF + 16384, sbase + STG_OFF, 3 + warp, 16, 7, lane);
      named_bar<5, 224>();
      if (t == 0) TS(tile ? 16 : 13);
      aux_kv_o(P, sbase, cta, tile, tile ? hpB : hpA, sb1, t, bud, g_tb_local);
      if (t == 0) TS(tile ? 17 : 15);
      if (tile == 0) {
        mbar_wait(sbase + BAR_STG_FULL, 1, bud);
        gelu_pass(sbase, g_uT + (size_t)fb2 * 224 * D_ + db2 * 128, t);
        if (t == 0) TS(18);
        named_bar<5, 224>();
        if (t == 0) {
          mbar_arrive(sbase + BAR_STG_EMPTY);
          red_release_add(&g_sync.u_cnt[dp2 * 2 + (fb2 >> 3)][0], 1);
          TS(14);
        }
      }
    }
    if (t == 0) {
      finish_role();
      mbar_wait(sbase + BAR_XSENT, 0, bud);
      red_release_add(&g_sync.x_flag[cta][0], 1);
      wait_counter(&g_sync.x_flag[cta ^ 2][0], 1, bud);
      g_sync.x_flag[cta ^ 2][0] = 0;
      mbar_arrive(sbase + BAR_XRECV);
    }
  } else {
    reg_alloc<160>();
    const int warp = t >> 5, lane = t & 31;
    const bool elected = (t == 0);
    const uint32_t peer_empty = mapa(sbase + BAR_EMPTY, rank ^ 1);
    const uint32_t stg = sbase + STG_OFF;
    cluster_wait();
    if (tid == 0) TS(59);
#pragma unroll 1
    for (int tile = 0; tile < 2; tile++) {
      {
        float acc[96], dummy[1];
        acc_zero(acc);
        mma_phase<1>(acc, dummy, tile ? 80 : 0, 16, sbase, wg, elected, peer_empty, bud);
        if (tid == 0) TS(tile ? 4 : 0);
        float p[4][16];
#pragma unroll
        for (int i = 0; i < 4; i++) acc_zero(p[i]);
        uint32_t af[32];
#pragma unroll
        for (int i = 0; i < 32; i++) af[i] = pack_bf16(acc[2 * i], acc[2 * i + 1]);
        if (tile == 0) mbar_wait(sbase + BAR_WPHI, 0, bud);
        wgmma_fence();
#pragma unroll
        for (int i = 0; i < 4; i++)
#pragma unroll
          for (int kk = 0; kk < 2; kk++)
            wgmma_rs_n32<1>(p[i], af[i * 8 + kk * 4], af[i * 8 + kk * 4 + 1], af[i * 8 + kk * 4 + 2], af[i * 8 + kk * 4 + 3],
                            make_desc(sbase + WPHI_OFF + tile * 4096 + (i & 1) * 2048 + kk * 1024, 1024, 512, 2), 1);
        wgmma_commit();
        if (tile == 1) mbar_wait(sbase + BAR_STG_EMPTY, 1, bud);
        const int row = wg * 64 + warp * 16 + (lane & 7) + 8 * ((lane >> 3) & 1);
#pragma unroll
        for (int c = 0; c < 4; c++) {
          const int chunk = 2 * (c & 1) + (lane >> 4);
          const float* a = &acc[64 + 8 * c];
          stmatrix_x4(stg + 32768 + (c >> 1) * 8192 + row * 64 + ((chunk ^ ((row >> 1) & 3)) << 4), pack_bf16(a[0], a[1]),
                      pack_bf16(a[2], a[3]), pack_bf16(a[4], a[5]), pack_bf16(a[6], a[7]));
        }
        sts128(stg + 49152 + tid * 32, 0x3F803F80u, 0x3F803F80u, 0x3F803F80u, 0x3F803F80u);
        sts128(stg + 49152 + tid * 32 + 16, 0x3F803F80u, 0x3F803F80u, 0x3F803F80u, 0x3F803F80u);
        wgmma_wait<0>();
        named_bar<4, 256>();
#pragma unroll
        for (int i = 0; i < 4; i++)
#pragma unroll
          for (int c = 0; c < 2; c++) {
            const int chunk = (i & 1) * 4 + 2 * c + (lane >> 4);
            const float* a = &p[i][8 * c];
            stmatrix_x4((i >> 1 ? stg + 16384 : sbase + PQ_OFF) + row * 128 + ((chunk ^ (row & 7)) << 4), pack_bf16(a[0], a[1]), pack_bf16(a[2], a[3]),
                        pack_bf16(a[4], a[5]), pack_bf16(a[6], a[7]));
          }
        fence_proxy_async_smem();
        mbar_arrive(sbase + BAR_STG_FULL);
        if (tid == 0) TS(tile ? 5 : 1);
      }
      if (tile == 0) {
        float acc[64], acc2[48];
        acc_zero(acc); acc_zero(acc2);
        mma_phase<2>(acc, acc2, 16, 64, sbase, wg, elected, peer_empty, bud);
        if (tid == 0) TS(2);
        mbar_wait(sbase + BAR_STG_EMPTY, 0, bud);
        const int mi = lane >> 3, i = lane & 7;
        const int dchunk = 2 * warp + (mi & 1);
        const uint32_t base = stg + wg * 28672 + (8 * (mi >> 1) + i) * 128 + ((dchunk ^ i) << 4);
#pragma unroll
        for (int c = 0; c < 8; c++)
          stmatrix_x4_t(base + c * 2048, pack_bf16(acc[8 * c], acc[8 * c + 1]), pack_bf16(acc[8 * c + 2], acc[8 * c + 3]),
                        pack_bf16(acc[8 * c + 4], acc[8 * c + 5]), pack_bf16(acc[8 * c + 6], acc[8 * c + 7]));
#pragma unroll
        for (int c = 0; c < 6; c++)
          stmatrix_x4_t(base + (8 + c) * 2048, pack_bf16(acc2[8 * c], acc2[8 * c + 1]), pack_bf16(acc2[8 * c + 2], acc2[8 * c + 3]),
                        pack_bf16(acc2[8 * c + 4], acc2[8 * c + 5]), pack_bf16(acc2[8 * c + 6], acc2[8 * c + 7]));
        mbar_arrive(sbase + BAR_STG_FULL);
        if (tid == 0) TS(3);
      }
    }
    float acc[64], acc2[64];
    acc_zero(acc); acc_zero(acc2);
    const uint32_t own = kh * 512;
    float dummy[1];
    mma_phase<3>(acc, acc2, 96, 56, sbase, wg, elected, peer_empty, bud, own);
    {
      if (tid == 0) TS(6);
      const uint32_t ga = sbase + GATE_OFF + 4 * (wg * 64 + warp * 16 + (lane >> 2));
      float m0, m1, b0, b1;
      asm volatile("ld.shared.f32 %0, [%1];" : "=f"(m0) : "r"(ga));
      asm volatile("ld.shared.f32 %0, [%1];" : "=f"(m1) : "r"(ga + 32));
      asm volatile("ld.shared.f32 %0, [%1];" : "=f"(b0) : "r"(ga + 512));
      asm volatile("ld.shared.f32 %0, [%1];" : "=f"(b1) : "r"(ga + 544));
      b0 *= m0; b1 *= m1;
#pragma unroll
      for (int j = 0; j < 16; j++) {
        acc2[4 * j] = fmaf(acc2[4 * j], m0, b0);
        acc2[4 * j + 1] = fmaf(acc2[4 * j + 1], m0, b0);
        acc2[4 * j + 2] = fmaf(acc2[4 * j + 2], m1, b1);
        acc2[4 * j + 3] = fmaf(acc2[4 * j + 3], m1, b1);
      }
#pragma unroll
      for (int j = 0; j < 16; j++) {
        acc[4 * j] = fmaf(acc[4 * j], m0, b0);
        acc[4 * j + 1] = fmaf(acc[4 * j + 1], m0, b0);
        acc[4 * j + 2] = fmaf(acc[4 * j + 2], m1, b1);
        acc[4 * j + 3] = fmaf(acc[4 * j + 3], m1, b1);
      }
    }
    mma_phase<4>(acc2, dummy, 152, 16, sbase, wg, elected, peer_empty, bud);
    if (tid == 0) TS(7);
    {
      uint4* dst = g_xch + (size_t)(cta * 2 + wg) * 1024 + t;
      const uint4* src = g_xch + (size_t)((cta ^ 2) * 2 + wg) * 1024 + t;
      const uint32_t s16 = (sbase & 0x3FFFF) >> 4;
      const uint32_t a_lo = s16 + wg * 256 + (256u << 16), b_lo = s16 + 512 + (256u << 16);
      uint4 rx[8];
#pragma unroll
      for (int i = 0; i < 16; i++) {
        const int e = 168 + i;
        const uint32_t o = c_ring.off16[e];
        mbar_wait(sbase + BAR_FULL + 8 * (e & 7), (e >> 3) & 1, bud);
        wgmma_fence();
#pragma unroll
        for (int kk = 0; kk < 2; kk++)
          wgmma_ss_n128<1, 1>(acc, desc64(a_lo + o + kk * 128, HI128), desc64(b_lo + o + kk * 128, HI128), 1);
        wgmma_commit();
        if (i < 2) {
#pragma unroll
          for (int q = 4 * i; q < 4 * i + 4; q++)
            dst[q * 128] = make_uint4(pack_bf16(acc2[8 * q], acc2[8 * q + 1]), pack_bf16(acc2[8 * q + 2], acc2[8 * q + 3]),
                                      pack_bf16(acc2[8 * q + 4], acc2[8 * q + 5]), pack_bf16(acc2[8 * q + 6], acc2[8 * q + 7]));
          if (i == 1) mbar_arrive(sbase + BAR_XSENT);
        }
        if (i == XRI) {
          if (tid == 0) TS(8);
          mbar_wait(sbase + BAR_XRECV, 0, bud);
          if (tid == 0) TS(9);
#pragma unroll
          for (int q = 0; q < 8; q++) rx[q] = __ldcg(src + q * 128);
        }
        wgmma_wait<1>();
        if (elected && i > 0 && e <= NENT - NB) {
          mbar_arrive(sbase + BAR_EMPTY + 8 * ((e + 7) & 7));
          mbar_arrive_remote(peer_empty + 8 * ((e + 7) & 7));
        }
      }
      mbar_wait(sbase + BAR_STG_EMPTY, 0, bud);
      wgmma_wait<0>();
      if (tid == 0) TS(58);
      const int row = warp * 16 + (lane & 7) + 8 * ((lane >> 3) & 1);
      const uint32_t ob = stg + wg * 16384;
#pragma unroll
      for (int c = 0; c < 8; c++) {
        const int chunk = 2 * (c & 3) + (lane >> 4);
        const float* a = &acc[8 * c];
        stmatrix_x4(ob + (c >> 2) * 8192 + row * 128 + ((chunk ^ (row & 7)) << 4), pack_bf16(a[0] + bf_lo(rx[c].x), a[1] + bf_hi(rx[c].x)),
                    pack_bf16(a[2] + bf_lo(rx[c].y), a[3] + bf_hi(rx[c].y)), pack_bf16(a[4] + bf_lo(rx[c].z), a[5] + bf_hi(rx[c].z)),
                    pack_bf16(a[6] + bf_lo(rx[c].w), a[7] + bf_hi(rx[c].w)));
      }
      fence_proxy_async_smem();
      if (wg == 0) named_bar<2, 128>(); else named_bar<3, 128>();
      if (elected) {
        const int col = db3 * 256 + kh * 128, r0 = sb3 * 128 + wg * 64;
        tma_store_2d(&P.out_st, ob, col, r0);
        tma_store_2d(&P.out_st, ob + 8192, col + 64, r0);
        bulk_commit();
        bulk_wait_read();
      }
      if (tid == 0) TS(10);
    }
  }
}

typedef CUresult (*PFN_encodeTiled)(CUtensorMap*, CUtensorMapDataType, cuuint32_t, void*, const cuuint64_t*, const cuuint64_t*,
                                    const cuuint32_t*, const cuuint32_t*, CUtensorMapInterleave, CUtensorMapSwizzle,
                                    CUtensorMapL2promotion, CUtensorMapFloatOOBfill);

void make_map(PFN_encodeTiled enc, CUtensorMap* m, const void* base, int rank, uint64_t d0, uint64_t d1, uint64_t d2, uint64_t s1,
              uint64_t s2, uint32_t b0, uint32_t b1, uint32_t b2, CUtensorMapSwizzle swz) {
  cuuint64_t dims[3] = {d0, d1, d2}, strides[2] = {s1, s2};
  cuuint32_t box[3] = {b0, b1, b2}, es[3] = {1, 1, 1};
  enc(m, CU_TENSOR_MAP_DATA_TYPE_BFLOAT16, rank, const_cast<void*>(base), dims, strides, box, es, CU_TENSOR_MAP_INTERLEAVE_NONE, swz,
      CU_TENSOR_MAP_L2_PROMOTION_L2_256B, CU_TENSOR_MAP_FLOAT_OOB_FILL_NONE);
}

}

extern "C" void kernel_launch(void* const* d_in, const int* in_sizes, int n_in, void* d_out, int out_size) {
  static PFN_encodeTiled enc = nullptr;
  static void *p_h = nullptr, *p_uT = nullptr, *p_oT = nullptr;
  if (!enc) {
    void* fn = nullptr;
    cudaDriverEntryPointQueryResult st;
    cudaGetDriverEntryPoint("cuTensorMapEncodeTiled", &fn, cudaEnableDefault, &st);
    enc = (PFN_encodeTiled)fn;
    cudaGetSymbolAddress(&p_h, g_h);
    cudaGetSymbolAddress(&p_uT, g_uT);
    cudaGetSymbolAddress(&p_oT, g_oT);
    cudaFuncSetAttribute(fused_kernel, cudaFuncAttributeMaxDynamicSharedMemorySize, SMEM_BYTES);
  }
  const CUtensorMapSwizzle SW128 = CU_TENSOR_MAP_SWIZZLE_128B, SW64 = CU_TENSOR_MAP_SWIZZLE_64B;
  Params P;
  make_map(enc, &P.x, d_in[0], 2, 1024, 2048, 1, 2048, 0, 64, 128, 1, SW128);
  make_map(enc, &P.wqkv, d_in[1], 3, 1024, 1024, 3, 6144, 2048, 64, 32, 3, SW128);
  make_map(enc, &P.h, p_h, 3, 64, 2048, 16, 2048, 128, 64, 32, 2, SW128);
  make_map(enc, &P.w1, d_in[5], 3, 32, 2048, 112, 7168, 64, 32, 16, 7, SW64);
  make_map(enc, &P.w2, d_in[7], 3, 64, 3584, 32, 4096, 128, 64, 32, 2, SW128);
  make_map(enc, &P.uT, p_uT, 3, 64, 3584, 16, 2048, 128, 64, 32, 2, SW128);
  make_map(enc, &P.oT, p_oT, 3, 64, 1024, 32, 4096, 128, 64, 32, 2, SW128);
  make_map(enc, &P.wo, d_in[3], 3, 64, 1024, 16, 2048, 128, 64, 32, 1, SW128);
  make_map(enc, &P.oT_st, p_oT, 2, 2048, 1024, 1, 4096, 0, 64, 64, 1, SW128);
  make_map(enc, &P.out_st, d_out, 2, 1024, 2048, 1, 2048, 0, 64, 64, 1, SW128);
  make_map(enc, &P.wphi, d_in[2], 2, 32, 1024, 1, 64, 0, 32, 64, 1, SW64);
  P.xin = (const __nv_bfloat16*)d_in[0];
  P.wqkv_p = (const __nv_bfloat16*)d_in[1];
  P.w2_p = (const __nv_bfloat16*)d_in[7];
  P.b1 = (const __nv_bfloat16*)d_in[6];
  P.b2 = (const __nv_bfloat16*)d_in[8];
  P.gw = (const __nv_bfloat16*)d_in[9];
  fused_kernel<<<NCTA, 512, SMEM_BYTES, cudaStreamPerThread>>>(P);
}
```

```cpp
#include <cuda_runtime.h>
#include <cuda_bf16.h>
#include <cuda.h>
#include <stdint.h>

namespace {

constexpr int S_ = 2048, D_ = 1024, F_ = 3584;
constexpr int NCTA = 128;

constexpr uint32_t RING_BYTES = 163840;
constexpr uint32_t PQ_OFF = 147456;
constexpr uint32_t STG_OFF = RING_BYTES;
constexpr uint32_t STG_BYTES = 57344;
constexpr uint32_t WPHI_OFF = STG_OFF + STG_BYTES;
constexpr uint32_t B1_OFF = WPHI_OFF + 8192;
constexpr uint32_t GATE_OFF = B1_OFF + 1024;
constexpr uint32_t BAR_OFF = GATE_OFF + 1536;
constexpr uint32_t SMEM_BYTES = BAR_OFF + 256;
constexpr int NB = 8;
constexpr uint32_t BAR_FULL = BAR_OFF, BAR_EMPTY = BAR_OFF + 64, BAR_STG_FULL = BAR_OFF + 128,
                   BAR_STG_EMPTY = BAR_OFF + 136, BAR_WPHI = BAR_OFF + 144, BAR_XFREE = BAR_OFF + 152,
                   BAR_DEP = BAR_OFF + 160  , BAR_XSENT = BAR_OFF + 192, BAR_XRECV = BAR_OFF + 200;
constexpr uint32_t E1_BYTES = 40960, E2_BYTES = 22528, E3_BYTES = 24576, E4_BYTES = 16384;

struct SyncCtr {
  unsigned ln_cnt[32];
  unsigned done[32];
  unsigned u_cnt[8][32];
  unsigned kv_cnt[16][32];
  unsigned o_cnt[32][32];
  unsigned x_flag[NCTA][32];
};
__device__ SyncCtr g_sync;
__device__ __align__(1024) __nv_bfloat16 g_h[S_ * D_];
__device__ __align__(1024) __nv_bfloat16 g_uT[F_ * D_];
__device__ __align__(1024) __nv_bfloat16 g_oT[D_ * S_];
__device__ __align__(1024) float g_kv[32 * 2560];
__device__ __align__(1024) float g_gate[2 * S_];
__device__ __align__(1024) uint4 g_xch[NCTA * 2048];

struct Params {
  CUtensorMap x, wqkv, h, w1, w2, uT, oT, wo, oT_st, out_st, wphi;
  const __nv_bfloat16* xin;
  const __nv_bfloat16* b1;
  const __nv_bfloat16* b2;
  const __nv_bfloat16* gw;
};

__device__ __forceinline__ uint32_t smem_u32(const void* p) { return (uint32_t)__cvta_generic_to_shared(p); }
__device__ __forceinline__ void mbar_init(uint32_t bar, uint32_t count) {
  asm volatile("mbarrier.init.shared::cta.b64 [%0], %1;" ::"r"(bar), "r"(count));
}
__device__ __forceinline__ void mbar_expect_tx(uint32_t bar, uint32_t bytes) {
  asm volatile("mbarrier.arrive.expect_tx.shared::cta.b64 _, [%0], %1;" ::"r"(bar), "r"(bytes) : "memory");
}
__device__ __forceinline__ void mbar_arrive(uint32_t bar) {
  asm volatile("mbarrier.arrive.shared::cta.b64 _, [%0];" ::"r"(bar) : "memory");
}
__device__ __forceinline__ uint32_t mapa(uint32_t addr, uint32_t cta) {
  uint32_t r;
  asm volatile("mapa.shared::cluster.u32 %0, %1, %2;" : "=r"(r) : "r"(addr), "r"(cta));
  return r;
}
__device__ __forceinline__ void mbar_arrive_remote(uint32_t remote_bar) {
  asm volatile("mbarrier.arrive.shared::cluster.b64 _, [%0];" ::"r"(remote_bar) : "memory");
}
__device__ __forceinline__ bool mbar_try_wait(uint32_t bar, uint32_t parity) {
  uint32_t ok;
  asm volatile("{\n.reg .pred p;\nmbarrier.try_wait.parity.shared::cta.b64 p, [%1], %2;\nselp.u32 %0, 1, 0, p;\n}\n"
               : "=r"(ok) : "r"(bar), "r"(parity) : "memory");
  return ok;
}
constexpr uint32_t SPIN_LIMIT = 1u << 24;
__device__ __forceinline__ void mbar_wait(uint32_t bar, uint32_t parity, uint32_t& bud) {
  while (!mbar_try_wait(bar, parity)) {
    if (++bud > SPIN_LIMIT) break;
  }
}
__device__ __forceinline__ void tma_load_2d(uint32_t dst, const CUtensorMap* tm, uint32_t bar, int c0, int c1) {
  asm volatile("cp.async.bulk.tensor.2d.shared::cluster.global.mbarrier::complete_tx::bytes [%0], [%1, {%3, %4}], [%2];"
               ::"r"(dst), "l"(tm), "r"(bar), "r"(c0), "r"(c1) : "memory");
}
__device__ __forceinline__ void tma_load_3d(uint32_t dst, const CUtensorMap* tm, uint32_t bar, int c0, int c1, int c2) {
  asm volatile("cp.async.bulk.tensor.3d.shared::cluster.global.mbarrier::complete_tx::bytes [%0], [%1, {%3, %4, %5}], [%2];"
               ::"r"(dst), "l"(tm), "r"(bar), "r"(c0), "r"(c1), "r"(c2) : "memory");
}
__device__ __forceinline__ void tma_load_3d_mc(uint32_t dst, const CUtensorMap* tm, uint32_t bar, int c0, int c1, int c2, uint16_t mask) {
  asm volatile("cp.async.bulk.tensor.3d.shared::cluster.global.mbarrier::complete_tx::bytes.multicast::cluster [%0], [%1, {%3, %4, %5}], [%2], %6;"
               ::"r"(dst), "l"(tm), "r"(bar), "r"(c0), "r"(c1), "r"(c2), "h"(mask) : "memory");
}
__device__ __forceinline__ void tma_store_2d(const CUtensorMap* tm, uint32_t src, int c0, int c1) {
  asm volatile("cp.async.bulk.tensor.2d.global.shared::cta.bulk_group [%0, {%2, %3}], [%1];"
               ::"l"(tm), "r"(src), "r"(c0), "r"(c1) : "memory");
}
__device__ __forceinline__ void bulk_reduce_add_f32(float* dst, uint32_t src, uint32_t bytes) {
  asm volatile("cp.reduce.async.bulk.global.shared::cta.bulk_group.add.f32 [%0], [%1], %2;" ::"l"(dst), "r"(src), "r"(bytes) : "memory");
}
__device__ __forceinline__ bool elect_one() {
  uint32_t p;
  asm volatile("{\n.reg .pred q;\nelect.sync _|q, 0xffffffff;\nselp.u32 %0, 1, 0, q;\n}\n" : "=r"(p));
  return p;
}
__device__ __forceinline__ uint32_t max_bf2(uint32_t a, uint32_t b) { uint32_t r; asm("max.bf16x2 %0, %1, %2;" : "=r"(r) : "r"(a), "r"(b)); return r; }
__device__ __forceinline__ void sts128(uint32_t a, uint32_t x, uint32_t y, uint32_t z, uint32_t w) {
  asm volatile("st.shared.v4.u32 [%0], {%1, %2, %3, %4};" ::"r"(a), "r"(x), "r"(y), "r"(z), "r"(w) : "memory");
}
__device__ __forceinline__ void bulk_commit() { asm volatile("cp.async.bulk.commit_group;" ::: "memory"); }
__device__ __forceinline__ void bulk_wait_all() { asm volatile("cp.async.bulk.wait_group 0;" ::: "memory"); }
__device__ __forceinline__ void bulk_wait_read() { asm volatile("cp.async.bulk.wait_group.read 0;" ::: "memory"); }
__device__ __forceinline__ void fence_proxy_async() { asm volatile("fence.proxy.async;" ::: "memory"); }
__device__ __forceinline__ void fence_proxy_async_smem() { asm volatile("fence.proxy.async.shared::cta;" ::: "memory"); }
__device__ __forceinline__ void wgmma_fence() { asm volatile("wgmma.fence.sync.aligned;" ::: "memory"); }
__device__ __forceinline__ void wgmma_commit() { asm volatile("wgmma.commit_group.sync.aligned;" ::: "memory"); }
template <int N> __device__ __forceinline__ void wgmma_wait() { asm volatile("wgmma.wait_group.sync.aligned %0;" ::"n"(N) : "memory"); }
__device__ __forceinline__ void cluster_arrive_relaxed() { asm volatile("barrier.cluster.arrive.relaxed.aligned;" ::: "memory"); }
__device__ __forceinline__ void cluster_wait() { asm volatile("barrier.cluster.wait.acquire.aligned;" ::: "memory"); }
__device__ __forceinline__ uint32_t cluster_ctarank() { uint32_t r; asm volatile("mov.u32 %0, %%cluster_ctarank;" : "=r"(r)); return r; }
template <int ID, int N> __device__ __forceinline__ void named_bar() { asm volatile("bar.sync %0, %1;" ::"n"(ID), "n"(N) : "memory"); }
__device__ __forceinline__ uint64_t make_desc(uint32_t addr, uint32_t lbo, uint32_t sbo, uint32_t swz) {
  return (uint64_t)((addr & 0x3FFFF) >> 4) | ((uint64_t)(lbo >> 4) << 16) | ((uint64_t)(sbo >> 4) << 32) | ((uint64_t)swz << 62);
}
template <int R> __device__ __forceinline__ void reg_alloc() { asm volatile("setmaxnreg.inc.sync.aligned.u32 %0;" ::"n"(R)); }
template <int R> __device__ __forceinline__ void reg_dealloc() { asm volatile("setmaxnreg.dec.sync.aligned.u32 %0;" ::"n"(R)); }
__device__ __forceinline__ uint32_t pack_bf16(float lo, float hi) {
  uint32_t r;
  asm("cvt.rn.bf16x2.f32 %0, %1, %2;" : "=r"(r) : "f"(hi), "f"(lo));
  return r;
}
__device__ __forceinline__ float bf_lo(uint32_t v) { return __uint_as_float(v << 16); }
__device__ __forceinline__ float bf_hi(uint32_t v) { return __uint_as_float(v & 0xFFFF0000u); }
__device__ __forceinline__ float bf_round(float v) { return bf_lo(pack_bf16(v, v)); }
__device__ __forceinline__ void stmatrix_x4(uint32_t addr, uint32_t r0, uint32_t r1, uint32_t r2, uint32_t r3) {
  asm volatile("stmatrix.sync.aligned.m8n8.x4.shared.b16 [%0], {%1, %2, %3, %4};" ::"r"(addr), "r"(r0), "r"(r1), "r"(r2), "r"(r3) : "memory");
}
__device__ __forceinline__ void stmatrix_x4_t(uint32_t addr, uint32_t r0, uint32_t r1, uint32_t r2, uint32_t r3) {
  asm volatile("stmatrix.sync.aligned.m8n8.x4.trans.shared.b16 [%0], {%1, %2, %3, %4};" ::"r"(addr), "r"(r0), "r"(r1), "r"(r2), "r"(r3) : "memory");
}
__device__ __forceinline__ float tanh_fast(float x) { float r; asm("tanh.approx.f32 %0, %1;" : "=f"(r) : "f"(x)); return r; }
__device__ __forceinline__ uint64_t desc64(uint32_t lo, uint32_t hi) {
  uint64_t d;
  asm("mov.b64 %0, {%1, %2};" : "=l"(d) : "r"(lo), "r"(hi));
  return d;
}
__device__ __forceinline__ unsigned ld_acquire(const unsigned* p) {
  unsigned v;
  asm volatile("ld.acquire.gpu.global.u32 %0, [%1];" : "=r"(v) : "l"(p) : "memory");
  return v;
}
__device__ __forceinline__ void red_release_add(unsigned* p, unsigned v) {
  asm volatile("red.release.gpu.global.add.u32 [%0], %1;" ::"l"(p), "r"(v) : "memory");
}
__device__ __forceinline__ void wait_counter(const unsigned* p, unsigned target, uint32_t& bud) {
  while (ld_acquire(p) < target) {
    __nanosleep(64);
    if (++bud > SPIN_LIMIT) break;
  }
}
__device__ __forceinline__ float ex2(float x) { float r; asm("ex2.approx.ftz.f32 %0, %1;" : "=f"(r) : "f"(x)); return r; }
__device__ __forceinline__ float rcp(float x) { float r; asm("rcp.approx.ftz.f32 %0, %1;" : "=f"(r) : "f"(x)); return r; }

template<int TA, int TB> __device__ __forceinline__ void wgmma_ss_n192(float (&d)[96], uint64_t da, uint64_t db, int scaleD) {
  asm volatile("{\n.reg .pred p;\nsetp.ne.b32 p, %98, 0;\n"
    "wgmma.mma_async.sync.aligned.m64n192k16.f32.bf16.bf16 {%0, %1, %2, %3, %4, %5, %6, %7, %8, %9, %10, %11, %12, %13, %14, %15, %16, %17, %18, %19, %20, %21, %22, %23, %24, %25, %26, %27, %28, %29, %30, %31, %32, %33, %34, %35, %36, %37, %38, %39, %40, %41, %42, %43, %44, %45, %46, %47, %48, %49, %50, %51, %52, %53, %54, %55, %56, %57, %58, %59, %60, %61, %62, %63, %64, %65, %66, %67, %68, %69, %70, %71, %72, %73, %74, %75, %76, %77, %78, %79, %80, %81, %82, %83, %84, %85, %86, %87, %88, %89, %90, %91, %92, %93, %94, %95}, %96, %97, p, 1, 1, %99, %100;\n}\n"
    : "+f"(d[0]), "+f"(d[1]), "+f"(d[2]), "+f"(d[3]), "+f"(d[4]), "+f"(d[5]), "+f"(d[6]), "+f"(d[7]), "+f"(d[8]), "+f"(d[9]), "+f"(d[10]), "+f"(d[11]), "+f"(d[12]), "+f"(d[13]), "+f"(d[14]), "+f"(d[15]), "+f"(d[16]), "+f"(d[17]), "+f"(d[18]), "+f"(d[19]), "+f"(d[20]), "+f"(d[21]), "+f"(d[22]), "+f"(d[23]), "+f"(d[24]), "+f"(d[25]), "+f"(d[26]), "+f"(d[27]), "+f"(d[28]), "+f"(d[29]), "+f"(d[30]), "+f"(d[31]), "+f"(d[32]), "+f"(d[33]), "+f"(d[34]), "+f"(d[35]), "+f"(d[36]), "+f"(d[37]), "+f"(d[38]), "+f"(d[39]), "+f"(d[40]), "+f"(d[41]), "+f"(d[42]), "+f"(d[43]), "+f"(d[44]), "+f"(d[45]), "+f"(d[46]), "+f"(d[47]), "+f"(d[48]), "+f"(d[49]), "+f"(d[50]), "+f"(d[51]), "+f"(d[52]), "+f"(d[53]), "+f"(d[54]), "+f"(d[55]), "+f"(d[56]), "+f"(d[57]), "+f"(d[58]), "+f"(d[59]), "+f"(d[60]), "+f"(d[61]), "+f"(d[62]), "+f"(d[63]), "+f"(d[64]), "+f"(d[65]), "+f"(d[66]), "+f"(d[67]), "+f"(d[68]), "+f"(d[69]), "+f"(d[70]), "+f"(d[71]), "+f"(d[72]), "+f"(d[73]), "+f"(d[74]), "+f"(d[75]), "+f"(d[76]), "+f"(d[77]), "+f"(d[78]), "+f"(d[79]), "+f"(d[80]), "+f"(d[81]), "+f"(d[82]), "+f"(d[83]), "+f"(d[84]), "+f"(d[85]), "+f"(d[86]), "+f"(d[87]), "+f"(d[88]), "+f"(d[89]), "+f"(d[90]), "+f"(d[91]), "+f"(d[92]), "+f"(d[93]), "+f"(d[94]), "+f"(d[95])
    : "l"(da), "l"(db), "r"(scaleD), "n"(TA), "n"(TB));
}

template<int TA, int TB> __device__ __forceinline__ void wgmma_ss_n128(float (&d)[64], uint64_t da, uint64_t db, int scaleD) {
  asm volatile("{\n.reg .pred p;\nsetp.ne.b32 p, %66, 0;\n"
    "wgmma.mma_async.sync.aligned.m64n128k16.f32.bf16.bf16 {%0, %1, %2, %3, %4, %5, %6, %7, %8, %9, %10, %11, %12, %13, %14, %15, %16, %17, %18, %19, %20, %21, %22, %23, %24, %25, %26, %27, %28, %29, %30, %31, %32, %33, %34, %35, %36, %37, %38, %39, %40, %41, %42, %43, %44, %45, %46, %47, %48, %49, %50, %51, %52, %53, %54, %55, %56, %57, %58, %59, %60, %61, %62, %63}, %64, %65, p, 1, 1, %67, %68;\n}\n"
    : "+f"(d[0]), "+f"(d[1]), "+f"(d[2]), "+f"(d[3]), "+f"(d[4]), "+f"(d[5]), "+f"(d[6]), "+f"(d[7]), "+f"(d[8]), "+f"(d[9]), "+f"(d[10]), "+f"(d[11]), "+f"(d[12]), "+f"(d[13]), "+f"(d[14]), "+f"(d[15]), "+f"(d[16]), "+f"(d[17]), "+f"(d[18]), "+f"(d[19]), "+f"(d[20]), "+f"(d[21]), "+f"(d[22]), "+f"(d[23]), "+f"(d[24]), "+f"(d[25]), "+f"(d[26]), "+f"(d[27]), "+f"(d[28]), "+f"(d[29]), "+f"(d[30]), "+f"(d[31]), "+f"(d[32]), "+f"(d[33]), "+f"(d[34]), "+f"(d[35]), "+f"(d[36]), "+f"(d[37]), "+f"(d[38]), "+f"(d[39]), "+f"(d[40]), "+f"(d[41]), "+f"(d[42]), "+f"(d[43]), "+f"(d[44]), "+f"(d[45]), "+f"(d[46]), "+f"(d[47]), "+f"(d[48]), "+f"(d[49]), "+f"(d[50]), "+f"(d[51]), "+f"(d[52]), "+f"(d[53]), "+f"(d[54]), "+f"(d[55]), "+f"(d[56]), "+f"(d[57]), "+f"(d[58]), "+f"(d[59]), "+f"(d[60]), "+f"(d[61]), "+f"(d[62]), "+f"(d[63])
    : "l"(da), "l"(db), "r"(scaleD), "n"(TA), "n"(TB));
}

template<int TA, int TB> __device__ __forceinline__ void wgmma_ss_n96(float (&d)[48], uint64_t da, uint64_t db, int scaleD) {
  asm volatile("{\n.reg .pred p;\nsetp.ne.b32 p, %50, 0;\n"
    "wgmma.mma_async.sync.aligned.m64n96k16.f32.bf16.bf16 {%0, %1, %2, %3, %4, %5, %6, %7, %8, %9, %10, %11, %12, %13, %14, %15, %16, %17, %18, %19, %20, %21, %22, %23, %24, %25, %26, %27, %28, %29, %30, %31, %32, %33, %34, %35, %36, %37, %38, %39, %40, %41, %42, %43, %44, %45, %46, %47}, %48, %49, p, 1, 1, %51, %52;\n}\n"
    : "+f"(d[0]), "+f"(d[1]), "+f"(d[2]), "+f"(d[3]), "+f"(d[4]), "+f"(d[5]), "+f"(d[6]), "+f"(d[7]), "+f"(d[8]), "+f"(d[9]), "+f"(d[10]), "+f"(d[11]), "+f"(d[12]), "+f"(d[13]), "+f"(d[14]), "+f"(d[15]), "+f"(d[16]), "+f"(d[17]), "+f"(d[18]), "+f"(d[19]), "+f"(d[20]), "+f"(d[21]), "+f"(d[22]), "+f"(d[23]), "+f"(d[24]), "+f"(d[25]), "+f"(d[26]), "+f"(d[27]), "+f"(d[28]), "+f"(d[29]), "+f"(d[30]), "+f"(d[31]), "+f"(d[32]), "+f"(d[33]), "+f"(d[34]), "+f"(d[35]), "+f"(d[36]), "+f"(d[37]), "+f"(d[38]), "+f"(d[39]), "+f"(d[40]), "+f"(d[41]), "+f"(d[42]), "+f"(d[43]), "+f"(d[44]), "+f"(d[45]), "+f"(d[46]), "+f"(d[47])
    : "l"(da), "l"(db), "r"(scaleD), "n"(TA), "n"(TB));
}

template<int TA, int TB> __device__ __forceinline__ void wgmma_ss_n40(float (&d)[20], uint64_t da, uint64_t db, int scaleD) {
  asm volatile("{\n.reg .pred p;\nsetp.ne.b32 p, %22, 0;\n"
    "wgmma.mma_async.sync.aligned.m64n40k16.f32.bf16.bf16 {%0, %1, %2, %3, %4, %5, %6, %7, %8, %9, %10, %11, %12, %13, %14, %15, %16, %17, %18, %19}, %20, %21, p, 1, 1, %23, %24;\n}\n"
    : "+f"(d[0]), "+f"(d[1]), "+f"(d[2]), "+f"(d[3]), "+f"(d[4]), "+f"(d[5]), "+f"(d[6]), "+f"(d[7]), "+f"(d[8]), "+f"(d[9]), "+f"(d[10]), "+f"(d[11]), "+f"(d[12]), "+f"(d[13]), "+f"(d[14]), "+f"(d[15]), "+f"(d[16]), "+f"(d[17]), "+f"(d[18]), "+f"(d[19])
    : "l"(da), "l"(db), "r"(scaleD), "n"(TA), "n"(TB));
}

template<int TB> __device__ __forceinline__ void wgmma_rs_n32(float (&d)[16], uint32_t a0, uint32_t a1, uint32_t a2, uint32_t a3, uint64_t db, int scaleD) {
  asm volatile("{\n.reg .pred p;\nsetp.ne.b32 p, %21, 0;\n"
    "wgmma.mma_async.sync.aligned.m64n32k16.f32.bf16.bf16 {%0, %1, %2, %3, %4, %5, %6, %7, %8, %9, %10, %11, %12, %13, %14, %15}, {%16, %17, %18, %19}, %20, p, 1, 1, %22;\n}\n"
    : "+f"(d[0]), "+f"(d[1]), "+f"(d[2]), "+f"(d[3]), "+f"(d[4]), "+f"(d[5]), "+f"(d[6]), "+f"(d[7]), "+f"(d[8]), "+f"(d[9]), "+f"(d[10]), "+f"(d[11]), "+f"(d[12]), "+f"(d[13]), "+f"(d[14]), "+f"(d[15])
    : "r"(a0), "r"(a1), "r"(a2), "r"(a3), "l"(db), "r"(scaleD), "n"(TB));
}


template <int N> __device__ __forceinline__ void acc_zero(float (&a)[N]) {
#pragma unroll
  for (int i = 0; i < N; i++) asm volatile("mov.f32 %0, 0f00000000;" : "=f"(a[i]));
}

constexpr int EX0 = 96 + 56, EY0 = EX0 + 16, NENT = EY0 + 16;
constexpr int NFIRST = 1;
struct RingTab {
  unsigned short off16[NENT];
  unsigned char nwait[NENT];
};
constexpr RingTab make_ring_tab() {
  RingTab tb{};
  uint32_t lo[NENT] = {}, hi[NENT] = {};
  constexpr int first[6] = {0, 16, 80, 96, EX0, NENT};
  constexpr uint32_t size[5] = {E1_BYTES, E2_BYTES, E1_BYTES, E3_BYTES, E4_BYTES};
  constexpr int slots[5] = {4, 6, 4, 6, 8};
  int tail = 0;
  for (int p = 0; p < 5; p++) {
    int best = 0;
    long bestc = 0;
    for (int s0 = 0; s0 < slots[p]; s0++) {
      long c = 0;
      int run = -1;
      for (int i = 0; i < slots[p]; i++) {
        const uint32_t off = (uint32_t)((s0 + i) % slots[p]) * size[p];
        for (int t = 0; t < first[p]; t++)
          if (lo[t] < off + size[p] && off < hi[t] && t > run) run = t;
        c += run;
      }
      if (s0 == 0 || c < bestc) { bestc = c; best = s0; }
    }
    for (int e = first[p]; e < first[p + 1]; e++) {
      const uint32_t off = (uint32_t)((best + e - first[p]) % slots[p]) * size[p];
      int need = e - NB;
      for (int t = 0; t < e; t++)
        if (lo[t] < off + size[p] && off < hi[t] && t > need) need = t;
      lo[e] = off;
      hi[e] = off + size[p];
      tb.off16[e] = (unsigned short)(off >> 4);
      int nw = need + 1 - tail;
      if (nw < 0) nw = 0;
      tb.nwait[e] = (unsigned char)nw;
      tail += nw;
    }
  }
  return tb;
}
__constant__ RingTab c_ring = make_ring_tab();

constexpr uint32_t HI128 = 0x40000040u;
constexpr uint32_t HI64 = 0x80000020u;

template <int PH, int NA, int NBB>
__device__ __forceinline__ void mma_phase(float (&acc)[NA], float (&acc2)[NBB], const int e0, const int n, const uint32_t sbase,
                                          const int wg, const bool elected, const uint32_t peer_empty, uint32_t& bud, const uint32_t own = 0) {
  const uint32_t s16 = (sbase & 0x3FFFF) >> 4;
  const uint32_t a_lo = PH == 1 ? (s16 + wg * 512 + (1u << 16)) : (s16 + wg * 256 + (256u << 16));
  const uint32_t b_lo = PH == 1 ? (s16 + 1024 + (256u << 16)) : (PH == 2 ? (s16 + 512 + (64u << 16)) : (s16 + 512 + (256u << 16)));
#pragma unroll 1
  for (int e = e0; e < e0 + n; e++) {
    const uint32_t o = c_ring.off16[e];
    mbar_wait(sbase + BAR_FULL + 8 * (e & 7), (e >> 3) & 1, bud);
    wgmma_fence();
    if constexpr (PH == 1) {
#pragma unroll
      for (int kk = 0; kk < 4; kk++)
        wgmma_ss_n192<0, 1>(acc, desc64(a_lo + o + kk * 2, HI128), desc64(b_lo + o + (kk >> 1) * 768 + (kk & 1) * 128, HI128), 1);
    } else if constexpr (PH == 2) {
#pragma unroll
      for (int kk = 0; kk < 2; kk++) {
        const uint64_t da = desc64(a_lo + o + kk * 128, HI128);
        wgmma_ss_n128<1, 1>(acc, da, desc64(b_lo + o + kk * 448, HI64), 1);
        wgmma_ss_n96<1, 1>(acc2, da, desc64(b_lo + o + kk * 448 + 256, HI64), 1);
      }
    } else if constexpr (PH == 4) {
#pragma unroll
      for (int kk = 0; kk < 2; kk++)
        wgmma_ss_n128<1, 1>(acc, desc64(a_lo + o + kk * 128, HI128), desc64(b_lo + o + kk * 128, HI128), 1);
    } else {
#pragma unroll
      for (int kk = 0; kk < 2; kk++) {
        const uint64_t da = desc64(a_lo + o + kk * 128, HI128);
        wgmma_ss_n128<1, 1>(acc, da, desc64(b_lo + o + kk * 128 + own, HI128), 1);
        wgmma_ss_n128<1, 1>(acc2, da, desc64(b_lo + o + kk * 128 + (own ^ 512), HI128), 1);
      }
    }
    wgmma_commit();
    wgmma_wait<1>();
    if (elected && e > e0 && e <= NENT - NB) {
      const uint32_t pj = 8 * ((e + 7) & 7);
      mbar_arrive(sbase + BAR_EMPTY + pj);
      mbar_arrive_remote(peer_empty + pj);
    }
  }
  wgmma_wait<0>();
  if (elected && n > 0 && e0 + n <= NENT - NB) {
    const uint32_t pj = 8 * ((e0 + n + 7) & 7);
    mbar_arrive(sbase + BAR_EMPTY + pj);
    mbar_arrive_remote(peer_empty + pj);
  }
}

__device__ __forceinline__ void gate_scale(float (&a)[64], float m0, float m1, float b0, float b1) {
#pragma unroll
  for (int j = 0; j < 16; j++) {
    a[4 * j] = fmaf(a[4 * j], m0, b0);
    a[4 * j + 1] = fmaf(a[4 * j + 1], m0, b0);
    a[4 * j + 2] = fmaf(a[4 * j + 2], m1, b1);
    a[4 * j + 3] = fmaf(a[4 * j + 3], m1, b1);
  }
}

template <uint32_t SZ> __device__ __forceinline__ uint32_t prod_alloc(int e, int& tail, uint32_t sbase, bool lead, uint32_t& bud) {
  for (int nw = c_ring.nwait[e]; nw > 0; nw--) {
    mbar_wait(sbase + BAR_EMPTY + 8 * (tail & (NB - 1)), (tail >> 3) & 1, bud);
    tail++;
  }
  if (lead) mbar_expect_tx(sbase + BAR_FULL + 8 * (e & (NB - 1)), SZ);
  return sbase + ((uint32_t)c_ring.off16[e] << 4);
}

template <int NR> __device__ __forceinline__ void ln_rows(const Params& P, int row0, int rstep, int lane) {
  uint4 xv[NR][4];
#pragma unroll
  for (int q = 0; q < NR; q++)
#pragma unroll
    for (int i = 0; i < 4; i++) xv[q][i] = __ldg(reinterpret_cast<const uint4*>(P.xin + (size_t)(row0 + q * rstep) * D_) + i * 32 + lane);
  float sum[NR], dot[NR];
#pragma unroll
  for (int q = 0; q < NR; q++) { sum[q] = 0.f; dot[q] = 0.f; }
#pragma unroll
  for (int i = 0; i < 4; i++) {
    const uint4 gv = __ldg(reinterpret_cast<const uint4*>(P.gw) + i * 32 + lane);
    const uint32_t gs[4] = {gv.x, gv.y, gv.z, gv.w};
#pragma unroll
    for (int q = 0; q < NR; q++) {
      const uint32_t xs[4] = {xv[q][i].x, xv[q][i].y, xv[q][i].z, xv[q][i].w};
#pragma unroll
      for (int c = 0; c < 4; c++) {
        uint32_t p2;
        asm("mul.rn.bf16x2 %0, %1, %2;" : "=r"(p2) : "r"(xs[c]), "r"(gs[c]));
        sum[q] += bf_lo(xs[c]) + bf_hi(xs[c]);
        dot[q] += bf_lo(p2) + bf_hi(p2);
      }
    }
  }
#pragma unroll
  for (int o = 16; o > 0; o >>= 1)
#pragma unroll
    for (int q = 0; q < NR; q++) {
      sum[q] += __shfl_xor_sync(0xffffffffu, sum[q], o);
      dot[q] += __shfl_xor_sync(0xffffffffu, dot[q], o);
    }
  float var[NR];
#pragma unroll
  for (int q = 0; q < NR; q++) {
    sum[q] *= (1.0f / D_);
    var[q] = 0.f;
#pragma unroll
    for (int i = 0; i < 4; i++) {
      const uint32_t xs[4] = {xv[q][i].x, xv[q][i].y, xv[q][i].z, xv[q][i].w};
#pragma unroll
      for (int c = 0; c < 4; c++) {
        const float a = bf_lo(xs[c]) - sum[q], b = bf_hi(xs[c]) - sum[q];
        var[q] = fmaf(a, a, var[q]);
        var[q] = fmaf(b, b, var[q]);
      }
    }
  }
#pragma unroll
  for (int o = 16; o > 0; o >>= 1)
#pragma unroll
    for (int q = 0; q < NR; q++) var[q] += __shfl_xor_sync(0xffffffffu, var[q], o);
#pragma unroll
  for (int q = 0; q < NR; q++) {
    const int row = row0 + q * rstep;
    const uint32_t m2 = pack_bf16(sum[q], sum[q]);
    const float rs = 1.0f / bf_round(sqrtf(bf_round(bf_round(var[q] * (1.0f / D_)) + 1e-5f)));
#pragma unroll
    for (int i = 0; i < 4; i++) {
      const uint32_t xs[4] = {xv[q][i].x, xv[q][i].y, xv[q][i].z, xv[q][i].w};
      uint32_t hs[4];
#pragma unroll
      for (int c = 0; c < 4; c++) {
        uint32_t d2;
        asm("sub.rn.bf16x2 %0, %1, %2;" : "=r"(d2) : "r"(xs[c]), "r"(m2));
        hs[c] = pack_bf16(bf_lo(d2) * rs, bf_hi(d2) * rs);
      }
      reinterpret_cast<uint4*>(g_h + (size_t)row * D_)[i * 32 + lane] = make_uint4(hs[0], hs[1], hs[2], hs[3]);
    }
    if (lane == 0) {
      const float z = bf_round(dot[q]);
      const float e = __expf(-fabsf(z)), big = 1.0f / (1.0f + e);
      const float g = bf_round(z >= 0.f ? big : e * big);
      g_gate[row] = g;
      g_gate[S_ + row] = bf_round(1.0f - g);
    }
  }
}

__device__ __forceinline__ void gelu_pass(uint32_t sbase, __nv_bfloat16* dst, int w, int lane) {
  const int r4 = lane >> 3;
#pragma unroll 1
  for (int q = 0; q < 16; q += 2) {
    uint32_t v[2][4], b2[2];
#pragma unroll
    for (int i = 0; i < 2; i++) {
      const int g = w * 16 + q + i, pan = g >= 56, frow = (g - pan * 56) * 4 + r4;
      asm volatile("ld.shared.u32 %0, [%1];" : "=r"(b2[i]) : "r"(sbase + B1_OFF + 4 * frow));
      asm volatile("ld.shared.v4.u32 {%0, %1, %2, %3}, [%4];" : "=r"(v[i][0]), "=r"(v[i][1]), "=r"(v[i][2]), "=r"(v[i][3])
                   : "r"(sbase + STG_OFF + g * 512 + lane * 16));
    }
#pragma unroll
    for (int i = 0; i < 2; i++) {
      const int g = w * 16 + q + i, pan = g >= 56, frow = (g - pan * 56) * 4 + r4;
#pragma unroll
      for (int c = 0; c < 4; c++) {
        uint32_t u2;
        asm("add.rn.bf16x2 %0, %1, %2;" : "=r"(u2) : "r"(v[i][c]), "r"(b2[i]));
        const float u0 = bf_lo(u2), u1 = bf_hi(u2);
        constexpr float C1 = 0.7978845608028654f, C2 = C1 * 0.044715f;
        const float t0 = tanh_fast(u0 * fmaf(u0 * u0, C2, C1)), t1 = tanh_fast(u1 * fmaf(u1 * u1, C2, C1));
        v[i][c] = pack_bf16(u0 * fmaf(t0, 0.5f, 0.5f), u1 * fmaf(t1, 0.5f, 0.5f));
      }
      *reinterpret_cast<uint4*>(dst + (size_t)frow * D_ + pan * 64 + (((lane ^ frow) & 7) << 3)) = make_uint4(v[i][0], v[i][1], v[i][2], v[i][3]);
    }
  }
}

__device__ __forceinline__ void feature_unit(uint32_t src, uint32_t dst, int unit, int lane) {
  constexpr float L2E = 1.4426950408889634f;
  const int sgn = lane >> 4, hd = (lane >> 3) & 1, r7 = lane & 7, row = unit * 8 + r7;
  const uint32_t flip = sgn ? 0x80008000u : 0u;
  uint32_t x[16];
#pragma unroll
  for (int c = 0; c < 4; c++)
    asm volatile("ld.shared.v4.u32 {%0, %1, %2, %3}, [%4];" : "=r"(x[4 * c]), "=r"(x[4 * c + 1]), "=r"(x[4 * c + 2]), "=r"(x[4 * c + 3])
                 : "r"(src + row * 128 + (((hd * 4 + c) ^ r7) << 4)) : "memory");
  __syncwarp();
#pragma unroll
  for (int i = 0; i < 16; i++) x[i] ^= flip;
  uint32_t ma = max_bf2(x[0], x[1]), mb = max_bf2(x[2], x[3]);
#pragma unroll
  for (int i = 4; i < 16; i += 2) { ma = max_bf2(ma, x[i]); mb = max_bf2(mb, x[i + 1]); }
  ma = max_bf2(ma, mb);
  const float off = -fmaxf(bf_lo(ma), bf_hi(ma)) * L2E;
  float e[32], s0 = 0.f, s1 = 0.f;
#pragma unroll
  for (int i = 0; i < 16; i++) {
    e[2 * i] = ex2(fmaf(bf_lo(x[i]), L2E, off));
    e[2 * i + 1] = ex2(fmaf(bf_hi(x[i]), L2E, off));
    s0 += e[2 * i];
    s1 += e[2 * i + 1];
  }
  const float inv = rcp(s0 + s1);
  const uint32_t d = dst + hd * 16384 + row * 128;
#pragma unroll
  for (int c = 0; c < 4; c++)
    sts128(d + (((sgn * 4 + c) ^ r7) << 4), pack_bf16(e[8 * c] * inv, e[8 * c + 1] * inv), pack_bf16(e[8 * c + 2] * inv, e[8 * c + 3] * inv),
           pack_bf16(e[8 * c + 4] * inv, e[8 * c + 5] * inv), pack_bf16(e[8 * c + 6] * inv, e[8 * c + 7] * inv));
}
__device__ __forceinline__ void feature_range(uint32_t src, uint32_t dst, int u0, int u1, int ustep, int lane) {
#pragma unroll 1
  for (int u = u0; u < u1; u += ustep) feature_unit(src, dst, u, lane);
  fence_proxy_async_smem();
}

__device__ __forceinline__ void aux_kv_o(const Params& P, uint32_t sbase, int cta, int tile, int hp, int sb, int t, uint32_t& bud) {
  const uint32_t stg = sbase + STG_OFF;
  const int warp = t >> 5, lane = t & 31, g = lane >> 2, tq = lane & 3;
  {
    float kv[2][20];
    acc_zero(kv[0]); acc_zero(kv[1]);
    wgmma_fence();
#pragma unroll
    for (int h = 0; h < 2; h++)
#pragma unroll
      for (int kk = 0; kk < 8; kk++)
        wgmma_ss_n40<1, 1>(kv[h], make_desc(stg + h * 16384 + kk * 2048, 4096, 1024, 1),
                           make_desc(stg + 32768 + h * 8192 + kk * 1024, 16384 - h * 8192, 512, 2), 1);
    wgmma_commit();
    wgmma_wait<0>();
    named_bar<6, 224>();
#pragma unroll
    for (int h = 0; h < 2; h++)
#pragma unroll
      for (int j = 0; j < 5; j++)
#pragma unroll
        for (int rh = 0; rh < 2; rh++)
          asm volatile("st.shared.v2.f32 [%0], {%1, %2};" ::"r"(stg + 32768 + h * 10240 + ((warp * 16 + g + 8 * rh) * 40 + 8 * j + 2 * tq) * 4),
                       "f"(kv[h][4 * j + 2 * rh]), "f"(kv[h][4 * j + 2 * rh + 1]) : "memory");
    fence_proxy_async_smem();
    named_bar<1, 128>();
    if (warp == 0) {
      if (t == 0) {
#pragma unroll 1
        for (int i = 0; i < 16; i++) {
          const int pc = (i + sb) & 15;
          bulk_reduce_add_f32(g_kv + hp * 5120 + pc * 320, stg + 32768 + pc * 1280, 1280);
        }
        bulk_commit();
        bulk_wait_all();
        red_release_add(&g_sync.kv_cnt[hp][0], 1);
        wait_counter(&g_sync.kv_cnt[hp][0], 16, bud);
      }
      __syncwarp();
    } else {
      feature_range(sbase + PQ_OFF, stg, 8 + warp, 16, 3, lane);
    }
    named_bar<5, 224>();
    if (t == 0 && tile == 0) {
      mbar_arrive(sbase + BAR_XFREE);
      mbar_arrive_remote(mapa(sbase + BAR_XFREE, cluster_ctarank() ^ 1));
    }
  }
  {
    float4 v[5][2];
#pragma unroll
    for (int i = 0; i < 5; i++) {
      const float4* src = reinterpret_cast<const float4*>(g_kv + hp * 5120) + (t + 128 * i) * 2;
      v[i][0] = __ldcg(src);
      v[i][1] = __ldcg(src + 1);
    }
#pragma unroll
    for (int i = 0; i < 5; i++) {
      const int idx = t + 128 * i, fr = idx / 5, c = idx - fr * 5;
      sts128(stg + 32768 + fr * 128 + ((c ^ (fr & 7)) << 4), pack_bf16(v[i][0].x, v[i][0].y), pack_bf16(v[i][0].z, v[i][0].w),
             pack_bf16(v[i][1].x, v[i][1].y), pack_bf16(v[i][1].z, v[i][1].w));
    }
  }
  fence_proxy_async_smem();
  named_bar<1, 128>();
  uint32_t op[2][16];
#pragma unroll
  for (int mb = 0; mb < 2; mb++) {
    float o[2][20];
    acc_zero(o[0]); acc_zero(o[1]);
    wgmma_fence();
#pragma unroll
    for (int h = 0; h < 2; h++)
#pragma unroll
      for (int c = 0; c < 4; c++)
        wgmma_ss_n40<0, 1>(o[h], make_desc(stg + h * 16384 + mb * 8192 + c * 32, 16, 1024, 1),
                           make_desc(stg + 32768 + h * 8192 + c * 2048, 4096, 1024, 1), 1);
    wgmma_commit();
    float g0, g1;
    asm volatile("ld.shared.f32 %0, [%1];" : "=f"(g0) : "r"(sbase + GATE_OFF + 1024 + 4 * (mb * 64 + warp * 16 + g)));
    asm volatile("ld.shared.f32 %0, [%1];" : "=f"(g1) : "r"(sbase + GATE_OFF + 1024 + 4 * (mb * 64 + warp * 16 + g + 8)));
    wgmma_wait<0>();
#pragma unroll
    for (int h = 0; h < 2; h++) {
      const float d0 = __shfl_sync(0xffffffffu, o[h][16], lane & ~3), d1 = __shfl_sync(0xffffffffu, o[h][18], lane & ~3);
      const float s0 = g0 * rcp(d0 + 1e-6f), s1 = g1 * rcp(d1 + 1e-6f);
#pragma unroll
      for (int j = 0; j < 4; j++) {
        op[mb][h * 8 + 2 * j] = pack_bf16(o[h][4 * j] * s0, o[h][4 * j + 1] * s0);
        op[mb][h * 8 + 2 * j + 1] = pack_bf16(o[h][4 * j + 2] * s1, o[h][4 * j + 3] * s1);
      }
    }
  }
  named_bar<1, 128>();
  {
    const int mi = lane >> 3, i = lane & 7, schunk = 2 * warp + (mi & 1);
#pragma unroll
    for (int mb = 0; mb < 2; mb++)
#pragma unroll
      for (int q = 0; q < 4; q++) {
        const int jrow = 16 * q + 8 * (mi >> 1) + i;
        stmatrix_x4_t(stg + mb * 8192 + jrow * 128 + ((schunk ^ i) << 4), op[mb][4 * q], op[mb][4 * q + 1], op[mb][4 * q + 2], op[mb][4 * q + 3]);
      }
  }
  fence_proxy_async_smem();
  named_bar<1, 128>();
  if (t == 0) {
    tma_store_2d(&P.oT_st, stg, sb * 128, hp * 64);
    tma_store_2d(&P.oT_st, stg + 8192, sb * 128 + 64, hp * 64);
    bulk_commit();
    bulk_wait_read();
    mbar_arrive(sbase + BAR_STG_EMPTY);
    bulk_wait_all();
    red_release_add(&g_sync.o_cnt[sb * 2 + tile][0], 1);
  }
}

__device__ __forceinline__ void watch(const unsigned* ctr, unsigned target, uint32_t bar, uint32_t& bud) {
  wait_counter(ctr, target, bud);
  fence_proxy_async();
  mbar_arrive(bar);
}

__device__ __forceinline__ void finish_role() {
  const unsigned old = atomicAdd(&g_sync.done[0], 1);
  if (old == 2 * NCTA - 1) {
    g_sync.ln_cnt[0] = 0;
    for (int i = 0; i < 8; i++) g_sync.u_cnt[i][0] = 0;
    for (int i = 0; i < 16; i++) g_sync.kv_cnt[i][0] = 0;
    for (int i = 0; i < 32; i++) g_sync.o_cnt[i][0] = 0;
    g_sync.done[0] = 0;
  }
}

__global__ void __cluster_dims__(2, 1, 1) __launch_bounds__(512, 1) fused_kernel(const __grid_constant__ Params P) {
  extern __shared__ __align__(1024) uint8_t smem_raw[];
  const uint32_t sbase = smem_u32(smem_raw);
  const int tid = threadIdx.x, t = tid & 127;
  const int wg = __shfl_sync(0xffffffffu, tid >> 7, 0);
  const uint32_t rank = cluster_ctarank();
  const int cta = blockIdx.x, cl = cta >> 1;
  uint32_t bud = 0;
  const int sb1 = (cl & 7) * 2 + rank, hpA = cl >> 3, hpB = hpA + 8;
  const int dp2 = cl & 3, fb2 = cl >> 2, db2 = dp2 * 2 + rank;
  const int kh = cl & 1, sb3 = ((cl >> 1) & 7) * 2 + rank, db3 = cl >> 4;
  constexpr int XP = 2;

  if (tid >= 384 && tid < 416) {
    if (tid == 384) {
      for (int i = 0; i < NFIRST; i++) mbar_init(sbase + BAR_FULL + 8 * i, 1);
      asm volatile("fence.mbarrier_init.release.cluster;" ::: "memory");
    }
    __syncwarp();
    asm volatile("bar.arrive 0, 512;" ::: "memory");
    cluster_arrive_relaxed();
    if (tid == 384) {
#pragma unroll
      for (int kt = 0; kt < NFIRST; kt++) {
        const uint32_t dst = sbase + kt * E1_BYTES, fb = sbase + BAR_FULL + 8 * kt;
        mbar_expect_tx(fb, E1_BYTES);
        tma_load_2d(dst, &P.x, fb, kt * 64, sb1 * 128);
        tma_load_3d(dst + 16384, &P.wqkv, fb, hpA * 64, kt * 64, 0);
        tma_load_3d(dst + 16384 + 12288, &P.wqkv, fb, hpA * 64, kt * 64 + 32, 0);
      }
    }
    __syncwarp();
  } else {
    if (tid == 416) {
      for (int i = NFIRST; i < NB; i++) mbar_init(sbase + BAR_FULL + 8 * i, 1);
      for (int i = 0; i < NB; i++) mbar_init(sbase + BAR_EMPTY + 8 * i, 4);
      mbar_init(sbase + BAR_STG_FULL, 256);
      mbar_init(sbase + BAR_STG_EMPTY, 1);
      mbar_init(sbase + BAR_WPHI, 1);
      for (int i = 0; i < 4; i++) mbar_init(sbase + BAR_DEP + 8 * i, 1);
      mbar_init(sbase + BAR_XSENT, 256);
      mbar_init(sbase + BAR_XRECV, 1);
      mbar_init(sbase + BAR_XFREE, 2);
      asm volatile("fence.mbarrier_init.release.cluster;" ::: "memory");
    }
    asm volatile("bar.sync 0, 512;" ::: "memory");
    cluster_arrive_relaxed();
  }

  if (wg == 3) {
    reg_dealloc<64>();
    const int warp = __shfl_sync(0xffffffffu, t >> 5, 0), lane = t & 31;
    if (warp == 0) {
      const bool lead = elect_one();
      cluster_wait();
      int e = NFIRST, tail = 0;
#pragma unroll 1
      for (int tile = 0; tile < 2; tile++) {
        const int hp = tile ? hpB : hpA;
        if (tile) mbar_wait(sbase + BAR_XFREE, 0, bud);
#pragma unroll 1
        for (int kt = tile ? 0 : NFIRST; kt < 16; kt++, e++) {
          const uint32_t dst = prod_alloc<E1_BYTES>(e, tail, sbase, lead, bud);
          const uint32_t fb = sbase + BAR_FULL + 8 * (e & (NB - 1));
          if (lead) {
            tma_load_2d(dst, &P.x, fb, kt * 64, sb1 * 128);
            tma_load_3d_mc(dst + 16384 + rank * 12288, &P.wqkv, fb, hp * 64, kt * 64 + rank * 32, 0, 3);
          }
        }
        if (tile == 0) {
          mbar_wait(sbase + BAR_DEP, 0, bud);
#pragma unroll 1
          for (int kt = 0; kt < 64; kt++, e++) {
            const uint32_t dst = prod_alloc<E2_BYTES>(e, tail, sbase, lead, bud);
            const uint32_t fb = sbase + BAR_FULL + 8 * (e & (NB - 1));
            if (lead) {
              tma_load_3d(dst, &P.h, fb, 0, kt * 32, db2 * 2);
              tma_load_3d_mc(dst + 8192 + rank * 7168, &P.w1, fb, 0, kt * 32 + rank * 16, fb2 * 7, 3);
            }
          }
        }
      }
      mbar_wait(sbase + BAR_DEP + 8, 0, bud);
#pragma unroll 1
      for (int kt = 0; kt < 56; kt++, e++) {
        const uint32_t dst = prod_alloc<E3_BYTES>(e, tail, sbase, lead, bud);
        const uint32_t fb = sbase + BAR_FULL + 8 * (e & (NB - 1));
        if (lead) {
          tma_load_3d(dst, &P.w2, fb, 0, kh * 1792 + kt * 32, sb3 * 2);
          tma_load_3d_mc(dst + 8192 + rank * 8192, &P.uT, fb, 0, kh * 1792 + kt * 32, db3 * 4 + rank * 2, 3);
        }
      }
#pragma unroll 1
      for (int q = 0; q < 2; q++) {
        const int cb = db3 * 4 + (q ^ kh ^ 1) * 2 + rank;
#pragma unroll 1
        for (int half = 0; half < 2; half++) {
          if (q == 0) {
            mbar_wait(sbase + BAR_DEP + 16 + 8 * half, 0, bud);
          }
#pragma unroll 1
          for (int kt = 0; kt < 8; kt++, e++) {
            const uint32_t dst = prod_alloc<E4_BYTES>(e, tail, sbase, lead, bud);
            const uint32_t fb = sbase + BAR_FULL + 8 * (e & (NB - 1));
            if (lead) {
              tma_load_3d(dst, &P.oT, fb, 0, half * 512 + kh * 256 + kt * 32, sb3 * 2);
              tma_load_3d_mc(dst + 8192 + rank * 4096, &P.wo, fb, 0, half * 512 + kh * 256 + kt * 32, cb, 3);
            }
          }
        }
      }
    } else {
      const int hw = warp - 1;
      ln_rows<1>(P, cta * 16 + 12 + hw, 0, lane);
      if (hw == 0) ln_rows<1>(P, cta * 16 + 15, 0, lane);
      named_bar<5, 224>();
      const bool watcher = (hw == 2 && lane == 0);
      if (watcher) watch(&g_sync.ln_cnt[0], NCTA, sbase + BAR_DEP, bud);
      __syncwarp();
#pragma unroll 1
      for (int tile = 0; tile < 2; tile++) {
        mbar_wait(sbase + BAR_STG_FULL, 0, bud);
        feature_range(sbase + STG_OFF + 16384, sbase + STG_OFF, 10 + 2 * hw, 12 + 2 * hw, 1, lane);
        named_bar<5, 224>();
        named_bar<6, 224>();
        feature_range(sbase + PQ_OFF, sbase + STG_OFF, hw, 9, 3, lane);
        named_bar<5, 224>();
        if (watcher) watch(&g_sync.o_cnt[sb3 * 2 + tile][0], 8, sbase + BAR_DEP + 16 + 8 * tile, bud);
        __syncwarp();
        if (tile == 0) {
          mbar_wait(sbase + BAR_STG_FULL, 1, bud);
          gelu_pass(sbase, g_uT + (size_t)fb2 * 224 * D_ + db2 * 128, 4 + hw, lane);
          named_bar<5, 224>();
          if (watcher) watch(&g_sync.u_cnt[db3 * 2 + kh][0], 16, sbase + BAR_DEP + 8, bud);
          __syncwarp();
        }
      }
      if (watcher) finish_role();
    }
  } else if (wg == 2) {
    cluster_wait();
    const int warp = t >> 5, lane = t & 31;
    if (t == 0) {
      mbar_expect_tx(sbase + BAR_WPHI, 8192);
      tma_load_2d(sbase + WPHI_OFF, &P.wphi, sbase + BAR_WPHI, 0, hpA * 64);
      tma_load_2d(sbase + WPHI_OFF + 4096, &P.wphi, sbase + BAR_WPHI, 0, hpB * 64);
    }
    for (int i = t; i < 160; i += 128) reinterpret_cast<float4*>(g_kv)[cta * 160 + i] = make_float4(0.f, 0.f, 0.f, 0.f);
    ln_rows<3>(P, cta * 16 + warp, 4, lane);
    named_bar<5, 224>();
    if (t == 0) red_release_add(&g_sync.ln_cnt[0], 1);
    for (int i = t; i < 224; i += 128) {
      const uint32_t bv = __bfloat16_as_ushort(P.b1[fb2 * 224 + i]);
      asm volatile("st.shared.u32 [%0], %1;" ::"r"(sbase + B1_OFF + 4 * i), "r"(bv * 0x10001u) : "memory");
    }
    if (t == 0) {
      wait_counter(&g_sync.ln_cnt[0], NCTA, bud);
      fence_proxy_async();
    }
    named_bar<1, 128>();
    {
      const float mg = __ldcg(g_gate + S_ + sb3 * 128 + t);
      const float b2v = kh ? 0.f : __bfloat162float(P.b2[sb3 * 128 + t]);
      asm volatile("st.shared.f32 [%0], %1;" ::"r"(sbase + GATE_OFF + 4 * t), "f"(mg) : "memory");
      asm volatile("st.shared.f32 [%0], %1;" ::"r"(sbase + GATE_OFF + 512 + 4 * t), "f"(b2v) : "memory");
      asm volatile("st.shared.f32 [%0], %1;" ::"r"(sbase + GATE_OFF + 1024 + 4 * t), "f"(__ldcg(g_gate + sb1 * 128 + t)) : "memory");
    }
#pragma unroll 1
    for (int tile = 0; tile < 2; tile++) {
      mbar_wait(sbase + BAR_STG_FULL, 0, bud);
      feature_range(sbase + STG_OFF + 16384, sbase + STG_OFF, warp ? 2 + 2 * warp : 0, 4 + 2 * warp, 1, lane);
      named_bar<5, 224>();
      aux_kv_o(P, sbase, cta, tile, tile ? hpB : hpA, sb1, t, bud);
      if (tile == 0) {
        mbar_wait(sbase + BAR_STG_FULL, 1, bud);
        gelu_pass(sbase, g_uT + (size_t)fb2 * 224 * D_ + db2 * 128, warp, lane);
        named_bar<5, 224>();
        if (t == 0) {
          mbar_arrive(sbase + BAR_STG_EMPTY);
          red_release_add(&g_sync.u_cnt[dp2 * 2 + (fb2 >> 3)][0], 1);
        }
      }
    }
    if (t == 0) {
      finish_role();
      mbar_wait(sbase + BAR_XSENT, 0, bud);
      red_release_add(&g_sync.x_flag[cta][0], 1);
      wait_counter(&g_sync.x_flag[cta ^ XP][0], 1, bud);
      g_sync.x_flag[cta ^ XP][0] = 0;
      mbar_arrive(sbase + BAR_XRECV);
    }
  } else {
    reg_alloc<160>();
    const int warp = t >> 5, lane = t & 31;
    const bool elected = (t == 0);
    const uint32_t peer_empty = mapa(sbase + BAR_EMPTY, rank ^ 1);
    const uint32_t stg = sbase + STG_OFF;
    cluster_wait();
#pragma unroll 1
    for (int tile = 0; tile < 2; tile++) {
      {
        float acc[96], dummy[1];
        acc_zero(acc);
        mma_phase<1>(acc, dummy, tile ? 80 : 0, 16, sbase, wg, elected, peer_empty, bud);
        if (wg == 0) asm volatile("bar.arrive 8, 256;" ::: "memory"); else asm volatile("bar.arrive 4, 256;" ::: "memory");
        float p[4][16];
#pragma unroll
        for (int i = 0; i < 4; i++) acc_zero(p[i]);
        uint32_t af[32];
#pragma unroll
        for (int i = 0; i < 32; i++) af[i] = pack_bf16(acc[2 * i], acc[2 * i + 1]);
        if (tile == 0) mbar_wait(sbase + BAR_WPHI, 0, bud);
        wgmma_fence();
#pragma unroll
        for (int i = 0; i < 4; i++)
#pragma unroll
          for (int kk = 0; kk < 2; kk++)
            wgmma_rs_n32<1>(p[i], af[i * 8 + kk * 4], af[i * 8 + kk * 4 + 1], af[i * 8 + kk * 4 + 2], af[i * 8 + kk * 4 + 3],
                            make_desc(sbase + WPHI_OFF + tile * 4096 + (i & 1) * 2048 + kk * 1024, 1024, 512, 2), 1);
        wgmma_commit();
        if (tile == 1) mbar_wait(sbase + BAR_STG_EMPTY, 1, bud);
        const int row = wg * 64 + warp * 16 + (lane & 7) + 8 * ((lane >> 3) & 1);
#pragma unroll
        for (int c = 0; c < 4; c++) {
          const int chunk = 2 * (c & 1) + (lane >> 4);
          const float* a = &acc[64 + 8 * c];
          stmatrix_x4(stg + 32768 + (c >> 1) * 8192 + row * 64 + ((chunk ^ ((row >> 1) & 3)) << 4), pack_bf16(a[0], a[1]),
                      pack_bf16(a[2], a[3]), pack_bf16(a[4], a[5]), pack_bf16(a[6], a[7]));
        }
        sts128(stg + 49152 + tid * 32, 0x3F803F80u, 0x3F803F80u, 0x3F803F80u, 0x3F803F80u);
        sts128(stg + 49152 + tid * 32 + 16, 0x3F803F80u, 0x3F803F80u, 0x3F803F80u, 0x3F803F80u);
        wgmma_wait<0>();
        if (wg == 0) named_bar<4, 256>(); else named_bar<8, 256>();
#pragma unroll
        for (int i = 0; i < 4; i++)
#pragma unroll
          for (int c = 0; c < 2; c++) {
            const int chunk = (i & 1) * 4 + 2 * c + (lane >> 4);
            const float* a = &p[i][8 * c];
            stmatrix_x4((i >> 1 ? stg + 16384 : sbase + PQ_OFF) + row * 128 + ((chunk ^ (row & 7)) << 4), pack_bf16(a[0], a[1]), pack_bf16(a[2], a[3]),
                        pack_bf16(a[4], a[5]), pack_bf16(a[6], a[7]));
          }
        fence_proxy_async_smem();
        mbar_arrive(sbase + BAR_STG_FULL);
      }
      if (tile == 0) {
        float acc[64], acc2[48];
        acc_zero(acc); acc_zero(acc2);
        mma_phase<2>(acc, acc2, 16, 64, sbase, wg, elected, peer_empty, bud);
        mbar_wait(sbase + BAR_STG_EMPTY, 0, bud);
        const int mi = lane >> 3, i = lane & 7;
        const int dchunk = 2 * warp + (mi & 1);
        const uint32_t base = stg + wg * 28672 + (8 * (mi >> 1) + i) * 128 + ((dchunk ^ i) << 4);
#pragma unroll
        for (int c = 0; c < 8; c++)
          stmatrix_x4_t(base + c * 2048, pack_bf16(acc[8 * c], acc[8 * c + 1]), pack_bf16(acc[8 * c + 2], acc[8 * c + 3]),
                        pack_bf16(acc[8 * c + 4], acc[8 * c + 5]), pack_bf16(acc[8 * c + 6], acc[8 * c + 7]));
#pragma unroll
        for (int c = 0; c < 6; c++)
          stmatrix_x4_t(base + (8 + c) * 2048, pack_bf16(acc2[8 * c], acc2[8 * c + 1]), pack_bf16(acc2[8 * c + 2], acc2[8 * c + 3]),
                        pack_bf16(acc2[8 * c + 4], acc2[8 * c + 5]), pack_bf16(acc2[8 * c + 6], acc2[8 * c + 7]));
        mbar_arrive(sbase + BAR_STG_FULL);
      }
    }
    float acc[64], acc2[64];
    acc_zero(acc); acc_zero(acc2);
    const uint32_t own = kh * 512;
    float dummy[1];
    mma_phase<3>(acc, acc2, 96, 56, sbase, wg, elected, peer_empty, bud, own);
    float m0, m1, b0, b1;
    {
      const uint32_t ga = sbase + GATE_OFF + 4 * (wg * 64 + warp * 16 + (lane >> 2));
      asm volatile("ld.shared.f32 %0, [%1];" : "=f"(m0) : "r"(ga));
      asm volatile("ld.shared.f32 %0, [%1];" : "=f"(m1) : "r"(ga + 32));
      asm volatile("ld.shared.f32 %0, [%1];" : "=f"(b0) : "r"(ga + 512));
      asm volatile("ld.shared.f32 %0, [%1];" : "=f"(b1) : "r"(ga + 544));
      b0 *= m0; b1 *= m1;
    }
    gate_scale(acc2, m0, m1, b0, b1);
    gate_scale(acc, m0, m1, b0, b1);
    mma_phase<4>(acc2, dummy, EX0, 16, sbase, wg, elected, peer_empty, bud);
    {
      uint4* dst = g_xch + (size_t)(cta * 2 + wg) * 1024 + t;
      const uint4* src = g_xch + (size_t)((cta ^ XP) * 2 + wg) * 1024 + t;
      const uint32_t s16 = (sbase & 0x3FFFF) >> 4;
      const uint32_t a_lo = s16 + wg * 256 + (256u << 16), b_lo = s16 + 512 + (256u << 16);
      uint4 rx[8];
#pragma unroll
      for (int i = 0; i < 16; i++) {
        const int e = EY0 + i;
        const uint32_t o = c_ring.off16[e];
        mbar_wait(sbase + BAR_FULL + 8 * (e & 7), (e >> 3) & 1, bud);
        wgmma_fence();
#pragma unroll
        for (int kk = 0; kk < 2; kk++)
          wgmma_ss_n128<1, 1>(acc, desc64(a_lo + o + kk * 128, HI128), desc64(b_lo + o + kk * 128, HI128), 1);
        wgmma_commit();
        if (i < 2) {
#pragma unroll
          for (int q = 4 * i; q < 4 * i + 4; q++)
            dst[q * 128] = make_uint4(pack_bf16(acc2[8 * q], acc2[8 * q + 1]), pack_bf16(acc2[8 * q + 2], acc2[8 * q + 3]),
                                      pack_bf16(acc2[8 * q + 4], acc2[8 * q + 5]), pack_bf16(acc2[8 * q + 6], acc2[8 * q + 7]));
          if (i == 1) mbar_arrive(sbase + BAR_XSENT);
        }
        if (i == 15) {
          mbar_wait(sbase + BAR_XRECV, 0, bud);
#pragma unroll
          for (int q = 0; q < 8; q++) rx[q] = __ldcg(src + q * 128);
        }
        wgmma_wait<1>();
        if (elected && i > 0 && e <= NENT - NB) {
          mbar_arrive(sbase + BAR_EMPTY + 8 * ((e + 7) & 7));
          mbar_arrive_remote(peer_empty + 8 * ((e + 7) & 7));
        }
      }
      mbar_wait(sbase + BAR_STG_EMPTY, 0, bud);
      wgmma_wait<0>();
      const int row = warp * 16 + (lane & 7) + 8 * ((lane >> 3) & 1);
      const uint32_t ob = stg + wg * 16384;
#pragma unroll
      for (int c = 0; c < 8; c++) {
        const int chunk = 2 * (c & 3) + (lane >> 4);
        const float* a = &acc[8 * c];
        stmatrix_x4(ob + (c >> 2) * 8192 + row * 128 + ((chunk ^ (row & 7)) << 4), pack_bf16(a[0] + bf_lo(rx[c].x), a[1] + bf_hi(rx[c].x)),
                    pack_bf16(a[2] + bf_lo(rx[c].y), a[3] + bf_hi(rx[c].y)), pack_bf16(a[4] + bf_lo(rx[c].z), a[5] + bf_hi(rx[c].z)),
                    pack_bf16(a[6] + bf_lo(rx[c].w), a[7] + bf_hi(rx[c].w)));
      }
      fence_proxy_async_smem();
      if (wg == 0) named_bar<2, 128>(); else named_bar<3, 128>();
      if (elected) {
        const int col = db3 * 256 + kh * 128, r0 = sb3 * 128 + wg * 64;
        tma_store_2d(&P.out_st, ob, col, r0);
        tma_store_2d(&P.out_st, ob + 8192, col + 64, r0);
        bulk_commit();
        bulk_wait_read();
      }
    }
  }
}

typedef CUresult (*PFN_encodeTiled)(CUtensorMap*, CUtensorMapDataType, cuuint32_t, void*, const cuuint64_t*, const cuuint64_t*,
                                    const cuuint32_t*, const cuuint32_t*, CUtensorMapInterleave, CUtensorMapSwizzle,
                                    CUtensorMapL2promotion, CUtensorMapFloatOOBfill);

void make_map(PFN_encodeTiled enc, CUtensorMap* m, const void* base, int rank, uint64_t d0, uint64_t d1, uint64_t d2, uint64_t s1,
              uint64_t s2, uint32_t b0, uint32_t b1, uint32_t b2, CUtensorMapSwizzle swz) {
  cuuint64_t dims[3] = {d0, d1, d2}, strides[2] = {s1, s2};
  cuuint32_t box[3] = {b0, b1, b2}, es[3] = {1, 1, 1};
  enc(m, CU_TENSOR_MAP_DATA_TYPE_BFLOAT16, rank, const_cast<void*>(base), dims, strides, box, es, CU_TENSOR_MAP_INTERLEAVE_NONE, swz,
      CU_TENSOR_MAP_L2_PROMOTION_L2_256B, CU_TENSOR_MAP_FLOAT_OOB_FILL_NONE);
}

}

extern "C" void kernel_launch(void* const* d_in, const int* in_sizes, int n_in, void* d_out, int out_size) {
  static PFN_encodeTiled enc = nullptr;
  static void *p_h = nullptr, *p_uT = nullptr, *p_oT = nullptr;
  if (!enc) {
    void* fn = nullptr;
    cudaDriverEntryPointQueryResult st;
    cudaGetDriverEntryPoint("cuTensorMapEncodeTiled", &fn, cudaEnableDefault, &st);
    enc = (PFN_encodeTiled)fn;
    cudaGetSymbolAddress(&p_h, g_h);
    cudaGetSymbolAddress(&p_uT, g_uT);
    cudaGetSymbolAddress(&p_oT, g_oT);
    cudaFuncSetAttribute(fused_kernel, cudaFuncAttributeMaxDynamicSharedMemorySize, SMEM_BYTES);
  }
  const CUtensorMapSwizzle SW128 = CU_TENSOR_MAP_SWIZZLE_128B, SW64 = CU_TENSOR_MAP_SWIZZLE_64B;
  Params P;
  make_map(enc, &P.x, d_in[0], 2, 1024, 2048, 1, 2048, 0, 64, 128, 1, SW128);
  make_map(enc, &P.wqkv, d_in[1], 3, 1024, 1024, 3, 6144, 2048, 64, 32, 3, SW128);
  make_map(enc, &P.h, p_h, 3, 64, 2048, 16, 2048, 128, 64, 32, 2, SW128);
  make_map(enc, &P.w1, d_in[5], 3, 32, 2048, 112, 7168, 64, 32, 16, 7, SW64);
  make_map(enc, &P.w2, d_in[7], 3, 64, 3584, 32, 4096, 128, 64, 32, 2, SW128);
  make_map(enc, &P.uT, p_uT, 3, 64, 3584, 16, 2048, 128, 64, 32, 2, SW128);
  make_map(enc, &P.oT, p_oT, 3, 64, 1024, 32, 4096, 128, 64, 32, 2, SW128);
  make_map(enc, &P.wo, d_in[3], 3, 64, 1024, 16, 2048, 128, 64, 32, 1, SW128);
  make_map(enc, &P.oT_st, p_oT, 2, 2048, 1024, 1, 4096, 0, 64, 64, 1, SW128);
  make_map(enc, &P.out_st, d_out, 2, 1024, 2048, 1, 2048, 0, 64, 64, 1, SW128);
  make_map(enc, &P.wphi, d_in[2], 2, 32, 1024, 1, 64, 0, 32, 64, 1, SW64);
  P.xin = (const __nv_bfloat16*)d_in[0];
  P.b1 = (const __nv_bfloat16*)d_in[6];
  P.b2 = (const __nv_bfloat16*)d_in[8];
  P.gw = (const __nv_bfloat16*)d_in[9];
  fused_kernel<<<NCTA, 512, SMEM_BYTES, cudaStreamPerThread>>>(P);
}
```
